```python
import torch

def _softmax(x, axis=-1):
    return torch.softmax(x, dim=axis)
def _gelu(x):
    return torch.nn.functional.gelu(x, approximate="tanh")
def _silu(x):
    return torch.nn.functional.silu(x)
def _sigmoid(x):
    return torch.sigmoid(x)
def _layernorm(x, axis=-1, eps=1e-5):
    m = x.mean(dim=axis, keepdim=True)
    v = x.var(dim=axis, keepdim=True, unbiased=False)
    return (x - m) / torch.sqrt(v + eps)
def _scatter_add(tgt, idx, src, axis=0):
    return tgt.clone().index_add_(axis, idx, src)
def _segment_sum(src, seg, n):
    out = torch.zeros((n,) + src.shape[1:], dtype=src.dtype)
    return out.index_add_(0, seg, src)
def _pad(x, pw):
    flat = tuple(v for pair in reversed(pw) for v in pair)
    return torch.nn.functional.pad(x, flat)

kernel_name = 'interleave_layers__linear_kernel_hedgehog__glu_gated_glu__prompt'

def setup_inputs():

    _w = (lambda a: (lambda t: t.to(torch.bfloat16) if t.is_floating_point() else t)(torch.as_tensor(a)))
    def _A_setup():
        B, S, D, H = 1, 2048, 448, 16
        Dh = D // H
        return {
            "x": _w((lambda *s: torch.randn(*s, dtype=torch.bfloat16) * 0.05)(B, S, D)),
            "wqkv": _w((lambda *s: torch.randn(*s, dtype=torch.bfloat16) * 0.4)(D, 3 * D)),
            "w_phi": _w((lambda *s: torch.randn(*s, dtype=torch.bfloat16) * 0.4)(H, Dh, Dh) * (Dh ** -0.5)),
            "wo": _w((lambda *s: torch.randn(*s, dtype=torch.bfloat16) * 0.05)(D, D)),
        }
    _A_in = _A_setup()

    def _B_setup():
        B, S, D, F = 1, 2048, 448, 1792
        return {
            "x": _w((lambda *s: torch.randn(*s, dtype=torch.bfloat16) * 0.05)(B, S, D)),
            "w_gate": _w((lambda *s: torch.randn(*s, dtype=torch.bfloat16) * 0.05)(D, F)),
            "w_up": _w((lambda *s: torch.randn(*s, dtype=torch.bfloat16) * 0.05)(D, F)),
            "w_down": _w((lambda *s: torch.randn(*s, dtype=torch.bfloat16) * 0.05)(F, D)),
        }
    _B_in = _B_setup()

    return {
        "A_x": _A_in["x"],
        "A_wqkv": _A_in["wqkv"],
        "A_w_phi": _A_in["w_phi"],
        "A_wo": _A_in["wo"],
        "B_x": _B_in["x"],
        "B_w_gate": _B_in["w_gate"],
        "B_w_up": _B_in["w_up"],
        "B_w_down": _B_in["w_down"],
    }

def reference(A_x, A_wqkv, A_w_phi, A_wo, B_x, B_w_gate, B_w_up, B_w_down):
    def _A_ref(x, wqkv, w_phi, wo):
        B, S, D = x.shape
        H = 16; Dh = D // H
        qkv = (lambda x, *d: x.permute(*d))((x @ wqkv).reshape(B, S, 3, H, Dh), 2, 0, 3, 1, 4)
        q, k, v = qkv[0], qkv[1], qkv[2]
        pq = torch.einsum("bhsd,hdf->bhsf", q, w_phi)
        pk = torch.einsum("bhsd,hdf->bhsf", k, w_phi)
        phi_q = torch.concatenate([_softmax(pq, axis=-1), _softmax(-pq, axis=-1)], axis=-1)
        phi_k = torch.concatenate([_softmax(pk, axis=-1), _softmax(-pk, axis=-1)], axis=-1)
        kv = torch.einsum("bhsf,bhsd->bhfd", phi_k, v)
        z  = torch.einsum("bhsf->bhf", phi_k)
        num = torch.einsum("bhqf,bhfd->bhqd", phi_q, kv)
        den = torch.einsum("bhqf,bhf->bhq", phi_q, z)[..., None] + 1e-6
        o = num / den
        return (lambda x, *d: x.permute(*d))(o, 0, 2, 1, 3).reshape(B, S, D) @ wo

    def _B_ref(x, w_gate, w_up, w_down):
        g = torch.einsum("bsd,df->bsf", x, w_gate)
        u = torch.einsum("bsd,df->bsf", x, w_up)
        h = _sigmoid(g) * u
        return torch.einsum("bsf,fd->bsd", h, w_down)

    x = A_x
    x = x + _A_ref(_layernorm(x, axis=-1), A_wqkv, A_w_phi, A_wo)
    x = x + _B_ref(_layernorm(x, axis=-1), B_w_gate, B_w_up, B_w_down)
    x = x + _A_ref(_layernorm(x, axis=-1), A_wqkv, A_w_phi, A_wo)
    x = x + _B_ref(_layernorm(x, axis=-1), B_w_gate, B_w_up, B_w_down)
    return x
```

```cpp
#include <cuda_runtime.h>
#include <cuda_bf16.h>
#include <cuda.h>
#include <stdint.h>
#include <string.h>

#define DEVINL __device__ __forceinline__

extern __shared__ __align__(1024) unsigned char smem_raw[];

namespace hk {

constexpr int SEQ = 2048, DM = 448, FF = 1792;
constexpr int NRING = 6, STG = 16384;
constexpr int SM_A = 0;
constexpr int SM_RING = 7 * 16384;
constexpr int SM_KVB = SM_RING + NRING * STG;
constexpr int SM_WPHI = SM_KVB + 8192;
constexpr int SM_CS = SM_WPHI + 4096;
constexpr int SM_REDO = SM_CS + 240;
constexpr int SM_STATS = SM_CS + 2560;
constexpr int SM_BAR0 = SM_STATS + 1024;
constexpr int SM_TOTAL = SM_BAR0 + 896;
constexpr int NTHREADS = 512;
constexpr int QKV_BYTES = 64 * 192;
#define NT 4
#define WOA 2
#define WD1 180
#define WD2 1220
#define WD3 2420
#define WDH 100
#define KV1_D 50
#define XB 850
#define XB0 850
#define XC_T (B_AFULL + 13)
#define TLG 3

#define PK_T B_AFULL
#define PF_T B_WO
#define EARLY 3
#define YW 450
#define YJ 0
#define CSI 9
#define TK_D 372
constexpr int B_FULL = 0, B_CSQ = 6, B_COPIED = 7, B_EMPTY = 8, B_CSG = 14, B_KVSENT = 15, B_STATF = 16, B_AFULL = 18, B_HX0 = 32, B_HX1 = 34,
              B_STAGED = 36, B_AFREE = 40, B_AFREE2 = 42, B_STAGED1 = 44, B_ADDED = 48, B_CSF = 49, B_VERDICT = 50, B_WO = 51;

struct GrpScratch {
  uint32_t done[4][32];
  uint32_t rdy[32];
  uint32_t fin[32];
  uint32_t pad[64];
  uint2 chk[32][4];
};
struct MemScratch {
  uint32_t pk[32];
  uint32_t pad[224];
  uint4 cs[6 * 16 * 32];
  uint4 kv2[16 * 64];
  uint4 kv1[16 * 16 * 32];
};
struct Scratch {
  uint32_t sync[256];
  uint32_t tick[16 * 8 * 32];
  GrpScratch grp[16];
  MemScratch mem[8];
  uint4 wq[8 * 448 * 32];
  __nv_bfloat16 upd[SEQ * DM];
};
__device__ __align__(1024) Scratch g_scr;
#define TL(slot) do {} while (0)
#define TLW(w, slot) do {} while (0)
#define TLST(c, a, v) do {} while (0)
#define TLV(slot, val) do {} while (0)
#define TLARG(c, row, off)
#define TLG3() do {} while (0)
#define TL_EXTRA 0

struct Params {
  CUtensorMap m_x, m_qkv, m_qkv2, m_o64, m_upd, m_wo, m_woh, m_gu2[2], m_gu1[2], m_guh, m_wd128, m_wd64, m_wd32;
  const __nv_bfloat16* wd;
};
struct Ptrs {
  Scratch* S;
  const __nv_bfloat16 *wqkv, *wphi, *wg, *wu;
  __nv_bfloat16* out;
};

DEVINL uint32_t s2u(const void* p) { return (uint32_t)__cvta_generic_to_shared(p); }
DEVINL void mbar_init(uint32_t b, int c) { asm volatile("mbarrier.init.shared::cta.b64 [%0], %1;" ::"r"(b), "r"(c)); }
DEVINL void mbar_expect(uint32_t b, uint32_t bytes) {
  asm volatile("mbarrier.arrive.expect_tx.shared::cta.b64 _, [%0], %1;" ::"r"(b), "r"(bytes) : "memory");
}
DEVINL void mbar_arrive(uint32_t b) { asm volatile("mbarrier.arrive.shared::cta.b64 _, [%0];" ::"r"(b) : "memory"); }
DEVINL bool mbar_try(uint32_t b, uint32_t ph) {
  uint32_t ok;
  asm volatile("{.reg .pred p; mbarrier.try_wait.parity.shared::cta.b64 p, [%1], %2; selp.u32 %0,1,0,p;}"
               : "=r"(ok) : "r"(b), "r"(ph) : "memory");
  return ok;
}
DEVINL void mbar_wait(uint32_t b, uint32_t ph) {
  asm volatile(
      "{.reg .pred p; .reg .u32 n; mov.u32 n, 0;\n"
      "LW: mbarrier.try_wait.parity.shared::cta.b64 p, [%0], %1;\n"
      "@p bra LD; add.u32 n, n, 1; setp.lt.u32 p, n, 0x400000; @p bra LW; trap;\n"
      "LD: }\n" ::"r"(b), "r"(ph) : "memory");
}
DEVINL void mbar_wait2(uint32_t b0, uint32_t p0, uint32_t b1, uint32_t p1) {
  asm volatile(
      "{.reg .pred p, q; .reg .u32 n; mov.u32 n, 0;\n"
      "LW: mbarrier.try_wait.parity.shared::cta.b64 p, [%0], %1;\n"
      "mbarrier.try_wait.parity.shared::cta.b64 q, [%2], %3; and.pred p, p, q;\n"
      "@p bra LD; add.u32 n, n, 1; setp.lt.u32 p, n, 0x400000; @p bra LW; trap;\n"
      "LD: }\n" ::"r"(b0), "r"(p0), "r"(b1), "r"(p1) : "memory");
}
DEVINL uint32_t mapa(uint32_t a, uint32_t r) {
  uint32_t o;
  asm volatile("mapa.shared::cluster.u32 %0, %1, %2;" : "=r"(o) : "r"(a), "r"(r));
  return o;
}
DEVINL void mbar_arrive_remote(uint32_t b) { asm volatile("mbarrier.arrive.shared::cluster.b64 _, [%0];" ::"r"(b) : "memory"); }
DEVINL void st_async16(uint32_t dst, const uint32_t (&v)[4], uint32_t bar) {
  asm volatile("st.async.weak.shared::cluster.mbarrier::complete_tx::bytes.v4.b32 [%0], {%1,%2,%3,%4}, [%5];"
               ::"r"(dst), "r"(v[0]), "r"(v[1]), "r"(v[2]), "r"(v[3]), "r"(bar) : "memory");
}
DEVINL void lds16(uint32_t a, uint32_t (&v)[4]) {
  asm volatile("ld.shared.v4.u32 {%0,%1,%2,%3}, [%4];" : "=r"(v[0]), "=r"(v[1]), "=r"(v[2]), "=r"(v[3]) : "r"(a) : "memory");
}
DEVINL void cluster_arrive() { asm volatile("barrier.cluster.arrive.relaxed.aligned;" ::: "memory"); }
DEVINL void cluster_wait() { asm volatile("barrier.cluster.wait.acquire.aligned;" ::: "memory"); }
DEVINL bool elect_one() {
  uint32_t e;
  asm volatile("{.reg .pred P; elect.sync _|P, 0xffffffff; selp.u32 %0,1,0,P;}" : "=r"(e));
  return e;
}
DEVINL void tma4d(uint32_t dst, const CUtensorMap* m, int c0, int c1, int c2, int c3, uint32_t bar) {
  asm volatile("cp.async.bulk.tensor.4d.shared::cluster.global.mbarrier::complete_tx::bytes [%0], [%1, {%3, %4, %5, %6}], [%2];"
               ::"r"(dst), "l"(m), "r"(bar), "r"(c0), "r"(c1), "r"(c2), "r"(c3) : "memory");
}
DEVINL void expect1(uint32_t b, uint32_t bytes) {
  asm volatile("{.reg .pred P; elect.sync _|P, 0xffffffff; @P mbarrier.arrive.expect_tx.shared::cta.b64 _, [%0], %1;}" ::"r"(b), "r"(bytes) : "memory");
}
DEVINL void tma4d1(uint32_t dst, const CUtensorMap* m, int c0, int c1, int c2, int c3, uint32_t bar) {
  asm volatile("{.reg .pred P; elect.sync _|P, 0xffffffff;\n"
               "@P cp.async.bulk.tensor.4d.shared::cluster.global.mbarrier::complete_tx::bytes [%0], [%1, {%3, %4, %5, %6}], [%2];}"
               ::"r"(dst), "l"(m), "r"(bar), "r"(c0), "r"(c1), "r"(c2), "r"(c3) : "memory");
}
DEVINL void tma4d_mc(uint32_t dst, const CUtensorMap* m, int c0, int c1, uint32_t bar) {
  asm volatile("cp.async.bulk.tensor.4d.shared::cluster.global.mbarrier::complete_tx::bytes.multicast::cluster [%0], [%1, {%3, %4, %5, %5}], [%2], %6;"
               ::"r"(dst), "l"(m), "r"(bar), "r"(c0), "r"(c1), "r"(0), "h"((uint16_t)3) : "memory");
}
DEVINL void tma4d_mc1(uint32_t dst, const CUtensorMap* m, int c0, int c1, uint32_t bar) {
  asm volatile("{.reg .pred P; elect.sync _|P, 0xffffffff;\n"
               "@P cp.async.bulk.tensor.4d.shared::cluster.global.mbarrier::complete_tx::bytes.multicast::cluster [%0], [%1, {%3, %4, %5, %5}], [%2], %6;}"
               ::"r"(dst), "l"(m), "r"(bar), "r"(c0), "r"(c1), "r"(0), "h"((uint16_t)3) : "memory");
}
DEVINL void tma_add1(const CUtensorMap* m, int c0, int c1, uint32_t src) {
  asm volatile("{.reg .pred P; elect.sync _|P, 0xffffffff;\n"
               "@P cp.reduce.async.bulk.tensor.4d.global.shared::cta.add.tile.bulk_group [%0, {%1, %2, %3, %3}], [%4];}"
               ::"l"(m), "r"(c0), "r"(c1), "r"(0), "r"(src) : "memory");
}
DEVINL void count1(uint32_t* p, uint32_t src) {
  asm volatile("{.reg .pred P; elect.sync _|P, 0xffffffff;\n"
               "@P cp.reduce.async.bulk.global.shared::cta.bulk_group.add.u32 [%0], [%1], 16;}" ::"l"(p), "r"(src) : "memory");
}
DEVINL void tma_store(const CUtensorMap* m, int c0, int c1, uint32_t src) {
  asm volatile("cp.async.bulk.tensor.4d.global.shared::cta.tile.bulk_group [%0, {%1, %2, %3, %3}], [%4];"
               ::"l"(m), "r"(c0), "r"(c1), "r"(0), "r"(src) : "memory");
}
DEVINL void bulk_done() { asm volatile("cp.async.bulk.commit_group;\n cp.async.bulk.wait_group 0;" ::: "memory"); }
DEVINL void bulk_read() { asm volatile("cp.async.bulk.commit_group;\n cp.async.bulk.wait_group.read 0;" ::: "memory"); }
DEVINL void fence_async() { asm volatile("fence.proxy.async.shared::cta;" ::: "memory"); }
DEVINL void bar_sync(int id, int n) { asm volatile("bar.sync %0, %1;" ::"r"(id), "r"(n) : "memory"); }
DEVINL void wg_fence() { asm volatile("wgmma.fence.sync.aligned;" ::: "memory"); }
DEVINL void wg_commit() { asm volatile("wgmma.commit_group.sync.aligned;" ::: "memory"); }
template <int N> DEVINL void wg_wait() { asm volatile("wgmma.wait_group.sync.aligned %0;" ::"n"(N) : "memory"); }
DEVINL uint64_t mkdesc(uint32_t addr, uint32_t lbo, uint32_t sbo, int swz) {
  return (uint64_t)((addr & 0x3FFFF) >> 4) | ((uint64_t)(lbo >> 4) << 16) | ((uint64_t)(sbo >> 4) << 32) | ((uint64_t)swz << 62);
}
DEVINL uint32_t pack2(float lo, float hi) {
  uint32_t r;
  asm("cvt.rn.bf16x2.f32 %0, %1, %2;" : "=r"(r) : "f"(hi), "f"(lo));
  return r;
}
DEVINL uint32_t pack_tag(float lo, float hi, uint32_t tag) { return __byte_perm(__float_as_uint(lo) + ((tag ^ 1) << 16), pack2(0.f, hi), 0x7632); }
DEVINL float bf_lo(uint32_t w) { return __uint_as_float(w << 16); }
DEVINL float bf_hi(uint32_t w) { return __uint_as_float(w & 0xffff0000u); }
DEVINL uint32_t hsub2(uint32_t a, uint32_t b) { uint32_t r; asm("sub.rn.bf16x2 %0, %1, %2;" : "=r"(r) : "r"(a), "r"(b)); return r; }
DEVINL uint32_t hadd2(uint32_t a, uint32_t b) { uint32_t r; asm("add.rn.bf16x2 %0, %1, %2;" : "=r"(r) : "r"(a), "r"(b)); return r; }
DEVINL uint32_t hmul2(uint32_t a, uint32_t b) { uint32_t r; asm("mul.rn.bf16x2 %0, %1, %2;" : "=r"(r) : "r"(a), "r"(b)); return r; }
DEVINL uint32_t hfma2(uint32_t a, uint32_t b, uint32_t c) { uint32_t r; asm("fma.rn.bf16x2 %0, %1, %2, %3;" : "=r"(r) : "r"(a), "r"(b), "r"(c)); return r; }
DEVINL float ex2(float x) { float r; asm("ex2.approx.ftz.f32 %0, %1;" : "=f"(r) : "f"(x)); return r; }
DEVINL float tanh_fast(float x) { float r; asm("tanh.approx.f32 %0, %1;" : "=f"(r) : "f"(x)); return r; }
DEVINL float rsqrt_fast(float x) { float r; asm("rsqrt.approx.ftz.f32 %0, %1;" : "=f"(r) : "f"(x)); return r; }
DEVINL float rcp_fast(float x) { float r; asm("rcp.approx.ftz.f32 %0, %1;" : "=f"(r) : "f"(x)); return r; }
DEVINL void st_ll(void* p, uint32_t a, uint32_t b, uint32_t c, uint32_t d, uint32_t tag) {
  a = (a & ~1u) | tag;
  c = (c & ~1u) | tag;
  asm volatile("{.reg .b64 u, v; mov.b64 u, {%1,%2}; mov.b64 v, {%3,%4}; st.relaxed.gpu.global.v2.b64 [%0], {u, v};}"
               ::"l"(p), "r"(a), "r"(b), "r"(c), "r"(d) : "memory");
}
DEVINL void st_ll8(void* p, uint32_t a, uint32_t b, uint32_t tag) {
  a = (a & ~1u) | tag;
  asm volatile("{.reg .b64 u; mov.b64 u, {%1,%2}; st.relaxed.gpu.global.b64 [%0], u;}" ::"l"(p), "r"(a), "r"(b) : "memory");
}
template <int OFF> DEVINL void st_ll_o(void* p, uint32_t a, uint32_t b, uint32_t c, uint32_t d, uint32_t tag) {
  a = (a & ~1u) | tag;
  c = (c & ~1u) | tag;
  asm volatile("{.reg .b64 u, v; mov.b64 u, {%1,%2}; mov.b64 v, {%3,%4}; st.relaxed.gpu.global.v2.b64 [%0+%5], {u, v};}"
               ::"l"(p), "r"(a), "r"(b), "r"(c), "r"(d), "n"(OFF) : "memory");
}
template <int OFF> DEVINL uint4 ld_ll_o(const void* p) {
  uint4 v;
  asm volatile("{.reg .b64 u, v; ld.relaxed.gpu.global.v2.b64 {u, v}, [%4+%5]; mov.b64 {%0,%1}, u; mov.b64 {%2,%3}, v;}"
               : "=r"(v.x), "=r"(v.y), "=r"(v.z), "=r"(v.w) : "l"(p), "n"(OFF) : "memory");
  return v;
}
template <int OFF> DEVINL void ld_ll_miss(uint4& v, const void* p, uint32_t tag) {
  asm volatile("{.reg .b64 u, v; .reg .b32 x; .reg .pred q; lop3.b32 x, %0, %2, %6, 0x7e; and.b32 x, x, 1; setp.ne.u32 q, x, 0;\n"
               "mov.b64 u, {%0,%1}; mov.b64 v, {%2,%3}; @q ld.relaxed.gpu.global.v2.b64 {u, v}, [%4+%5]; mov.b64 {%0,%1}, u; mov.b64 {%2,%3}, v;}"
               : "+r"(v.x), "+r"(v.y), "+r"(v.z), "+r"(v.w) : "l"(p), "n"(OFF), "r"(tag) : "memory");
}
template <int OFF> DEVINL uint2 ld_ll8_o(const void* p) {
  uint2 v;
  asm volatile("{.reg .b64 u; ld.relaxed.gpu.global.b64 u, [%2+%3]; mov.b64 {%0,%1}, u;}" : "=r"(v.x), "=r"(v.y) : "l"(p), "n"(OFF) : "memory");
  return v;
}
DEVINL void st_flag(uint32_t* p, uint32_t v) { asm volatile("st.relaxed.gpu.global.u32 [%0], %1;" ::"l"(p), "r"(v) : "memory"); }
DEVINL void st_release(uint32_t* p, uint32_t v) { asm volatile("st.release.gpu.global.u32 [%0], %1;" ::"l"(p), "r"(v) : "memory"); }
DEVINL uint32_t ld_acquire(const uint32_t* p) {
  uint32_t v;
  asm volatile("ld.acquire.gpu.global.u32 %0, [%1];" : "=r"(v) : "l"(p) : "memory");
  return v;
}
DEVINL uint32_t ld_flag(const uint32_t* p) {
  uint32_t v;
  asm volatile("ld.relaxed.gpu.global.u32 %0, [%1];" : "=r"(v) : "l"(p) : "memory");
  return v;
}
DEVINL void short_wait(int cyc) {
  const uint32_t t = clock();
  while ((int)(clock() - t) < cyc) {}
}
template <int I> struct IC { static constexpr int value = I; };
template <int I, int N, class F> DEVINL void static_for(F&& f) {
  if constexpr (I < N) { f(IC<I>{}); static_for<I + 1, N>(f); }
}
DEVINL uint32_t tagchk(uint32_t a, uint32_t b, uint32_t t) {
  uint32_t r;
  asm("lop3.b32 %0, %1, %2, %3, 0x7e;" : "=r"(r) : "r"(a), "r"(b), "r"(t));
  return r;
}
DEVINL uint32_t or3(uint32_t a, uint32_t b, uint32_t c) {
  uint32_t r;
  asm("lop3.b32 %0, %1, %2, %3, 0xfe;" : "=r"(r) : "r"(a), "r"(b), "r"(c));
  return r;
}
DEVINL uint32_t chk4(const uint4* v, uint32_t t) {
  return or3(tagchk(v[0].x, v[0].z, t), tagchk(v[1].x, v[1].z, t), tagchk(v[2].x, v[2].z, t)) | tagchk(v[3].x, v[3].z, t);
}
DEVINL uint4 ld_nc16(const void* p) {
  uint4 v;
  asm volatile("ld.global.nc.v4.u32 {%0,%1,%2,%3}, [%4];" : "=r"(v.x), "=r"(v.y), "=r"(v.z), "=r"(v.w) : "l"(p));
  return v;
}
DEVINL void sts16(uint32_t a, const uint4& v) {
  asm volatile("st.shared.v4.u32 [%0], {%1,%2,%3,%4};" ::"r"(a), "r"(v.x), "r"(v.y), "r"(v.z), "r"(v.w) : "memory");
}
DEVINL float2 lds8(uint32_t a) {
  float2 v;
  asm volatile("ld.shared.v2.f32 {%0,%1}, [%2];" : "=f"(v.x), "=f"(v.y) : "r"(a) : "memory");
  return v;
}
DEVINL void stmat4(uint32_t a, uint32_t r0, uint32_t r1, uint32_t r2, uint32_t r3) {
  asm volatile("stmatrix.sync.aligned.m8n8.x4.shared.b16 [%0], {%1,%2,%3,%4};" ::"r"(a), "r"(r0), "r"(r1), "r"(r2), "r"(r3) : "memory");
}
DEVINL int my_tid() { int x; asm volatile("mov.u32 %0, %%tid.x;" : "=r"(x)); return x; }
DEVINL int opaque(int x) { asm volatile("" : "+r"(x)); return x; }
#define SPIN_GUARD(n) do { if (++(n) > (1 << 21)) __trap(); } while (0)

DEVINL void wg_ss_n192(float (&d)[96], uint64_t da, uint64_t db, int sd) {
  asm volatile("{.reg .pred p; setp.ne.b32 p, %98, 0;\n"
    "wgmma.mma_async.sync.aligned.m64n192k16.f32.bf16.bf16 {%0,%1,%2,%3,%4,%5,%6,%7,%8,%9,%10,%11,%12,%13,%14,%15,%16,%17,%18,%19,%20,%21,%22,%23,%24,%25,%26,%27,%28,%29,%30,%31,%32,%33,%34,%35,%36,%37,%38,%39,%40,%41,%42,%43,%44,%45,%46,%47,%48,%49,%50,%51,%52,%53,%54,%55,%56,%57,%58,%59,%60,%61,%62,%63,%64,%65,%66,%67,%68,%69,%70,%71,%72,%73,%74,%75,%76,%77,%78,%79,%80,%81,%82,%83,%84,%85,%86,%87,%88,%89,%90,%91,%92,%93,%94,%95}, %96, %97, p, 1, 1, 0, 1;}\n"
    : "+f"(d[0]),"+f"(d[1]),"+f"(d[2]),"+f"(d[3]),"+f"(d[4]),"+f"(d[5]),"+f"(d[6]),"+f"(d[7]),"+f"(d[8]),"+f"(d[9]),"+f"(d[10]),"+f"(d[11]),"+f"(d[12]),"+f"(d[13]),"+f"(d[14]),"+f"(d[15]),"+f"(d[16]),"+f"(d[17]),"+f"(d[18]),"+f"(d[19]),"+f"(d[20]),"+f"(d[21]),"+f"(d[22]),"+f"(d[23]),"+f"(d[24]),"+f"(d[25]),"+f"(d[26]),"+f"(d[27]),"+f"(d[28]),"+f"(d[29]),"+f"(d[30]),"+f"(d[31]),"+f"(d[32]),"+f"(d[33]),"+f"(d[34]),"+f"(d[35]),"+f"(d[36]),"+f"(d[37]),"+f"(d[38]),"+f"(d[39]),"+f"(d[40]),"+f"(d[41]),"+f"(d[42]),"+f"(d[43]),"+f"(d[44]),"+f"(d[45]),"+f"(d[46]),"+f"(d[47]),"+f"(d[48]),"+f"(d[49]),"+f"(d[50]),"+f"(d[51]),"+f"(d[52]),"+f"(d[53]),"+f"(d[54]),"+f"(d[55]),"+f"(d[56]),"+f"(d[57]),"+f"(d[58]),"+f"(d[59]),"+f"(d[60]),"+f"(d[61]),"+f"(d[62]),"+f"(d[63]),"+f"(d[64]),"+f"(d[65]),"+f"(d[66]),"+f"(d[67]),"+f"(d[68]),"+f"(d[69]),"+f"(d[70]),"+f"(d[71]),"+f"(d[72]),"+f"(d[73]),"+f"(d[74]),"+f"(d[75]),"+f"(d[76]),"+f"(d[77]),"+f"(d[78]),"+f"(d[79]),"+f"(d[80]),"+f"(d[81]),"+f"(d[82]),"+f"(d[83]),"+f"(d[84]),"+f"(d[85]),"+f"(d[86]),"+f"(d[87]),"+f"(d[88]),"+f"(d[89]),"+f"(d[90]),"+f"(d[91]),"+f"(d[92]),"+f"(d[93]),"+f"(d[94]),"+f"(d[95])
    : "l"(da), "l"(db), "r"(sd));
}
DEVINL void wg_ss_n184(float (&d)[92], uint64_t da, uint64_t db, int sd) {
  asm volatile("{.reg .pred p; setp.ne.b32 p, %94, 0;\n"
    "wgmma.mma_async.sync.aligned.m64n184k16.f32.bf16.bf16 {%0,%1,%2,%3,%4,%5,%6,%7,%8,%9,%10,%11,%12,%13,%14,%15,%16,%17,%18,%19,%20,%21,%22,%23,%24,%25,%26,%27,%28,%29,%30,%31,%32,%33,%34,%35,%36,%37,%38,%39,%40,%41,%42,%43,%44,%45,%46,%47,%48,%49,%50,%51,%52,%53,%54,%55,%56,%57,%58,%59,%60,%61,%62,%63,%64,%65,%66,%67,%68,%69,%70,%71,%72,%73,%74,%75,%76,%77,%78,%79,%80,%81,%82,%83,%84,%85,%86,%87,%88,%89,%90,%91}, %92, %93, p, 1, 1, 0, 1;}\n"
    : "+f"(d[0]),"+f"(d[1]),"+f"(d[2]),"+f"(d[3]),"+f"(d[4]),"+f"(d[5]),"+f"(d[6]),"+f"(d[7]),"+f"(d[8]),"+f"(d[9]),"+f"(d[10]),"+f"(d[11]),"+f"(d[12]),"+f"(d[13]),"+f"(d[14]),"+f"(d[15]),"+f"(d[16]),"+f"(d[17]),"+f"(d[18]),"+f"(d[19]),"+f"(d[20]),"+f"(d[21]),"+f"(d[22]),"+f"(d[23]),"+f"(d[24]),"+f"(d[25]),"+f"(d[26]),"+f"(d[27]),"+f"(d[28]),"+f"(d[29]),"+f"(d[30]),"+f"(d[31]),"+f"(d[32]),"+f"(d[33]),"+f"(d[34]),"+f"(d[35]),"+f"(d[36]),"+f"(d[37]),"+f"(d[38]),"+f"(d[39]),"+f"(d[40]),"+f"(d[41]),"+f"(d[42]),"+f"(d[43]),"+f"(d[44]),"+f"(d[45]),"+f"(d[46]),"+f"(d[47]),"+f"(d[48]),"+f"(d[49]),"+f"(d[50]),"+f"(d[51]),"+f"(d[52]),"+f"(d[53]),"+f"(d[54]),"+f"(d[55]),"+f"(d[56]),"+f"(d[57]),"+f"(d[58]),"+f"(d[59]),"+f"(d[60]),"+f"(d[61]),"+f"(d[62]),"+f"(d[63]),"+f"(d[64]),"+f"(d[65]),"+f"(d[66]),"+f"(d[67]),"+f"(d[68]),"+f"(d[69]),"+f"(d[70]),"+f"(d[71]),"+f"(d[72]),"+f"(d[73]),"+f"(d[74]),"+f"(d[75]),"+f"(d[76]),"+f"(d[77]),"+f"(d[78]),"+f"(d[79]),"+f"(d[80]),"+f"(d[81]),"+f"(d[82]),"+f"(d[83]),"+f"(d[84]),"+f"(d[85]),"+f"(d[86]),"+f"(d[87]),"+f"(d[88]),"+f"(d[89]),"+f"(d[90]),"+f"(d[91])
    : "l"(da), "l"(db), "r"(sd));
}
DEVINL void wg_ss_n184_z(float (&d)[92], uint64_t da, uint64_t db) {
  asm volatile("{.reg .pred p; setp.ne.b32 p, 0, 0;\n"
    "wgmma.mma_async.sync.aligned.m64n184k16.f32.bf16.bf16 {%0,%1,%2,%3,%4,%5,%6,%7,%8,%9,%10,%11,%12,%13,%14,%15,%16,%17,%18,%19,%20,%21,%22,%23,%24,%25,%26,%27,%28,%29,%30,%31,%32,%33,%34,%35,%36,%37,%38,%39,%40,%41,%42,%43,%44,%45,%46,%47,%48,%49,%50,%51,%52,%53,%54,%55,%56,%57,%58,%59,%60,%61,%62,%63,%64,%65,%66,%67,%68,%69,%70,%71,%72,%73,%74,%75,%76,%77,%78,%79,%80,%81,%82,%83,%84,%85,%86,%87,%88,%89,%90,%91}, %92, %93, p, 1, 1, 0, 1;}\n"
    : "=f"(d[0]),"=f"(d[1]),"=f"(d[2]),"=f"(d[3]),"=f"(d[4]),"=f"(d[5]),"=f"(d[6]),"=f"(d[7]),"=f"(d[8]),"=f"(d[9]),"=f"(d[10]),"=f"(d[11]),"=f"(d[12]),"=f"(d[13]),"=f"(d[14]),"=f"(d[15]),"=f"(d[16]),"=f"(d[17]),"=f"(d[18]),"=f"(d[19]),"=f"(d[20]),"=f"(d[21]),"=f"(d[22]),"=f"(d[23]),"=f"(d[24]),"=f"(d[25]),"=f"(d[26]),"=f"(d[27]),"=f"(d[28]),"=f"(d[29]),"=f"(d[30]),"=f"(d[31]),"=f"(d[32]),"=f"(d[33]),"=f"(d[34]),"=f"(d[35]),"=f"(d[36]),"=f"(d[37]),"=f"(d[38]),"=f"(d[39]),"=f"(d[40]),"=f"(d[41]),"=f"(d[42]),"=f"(d[43]),"=f"(d[44]),"=f"(d[45]),"=f"(d[46]),"=f"(d[47]),"=f"(d[48]),"=f"(d[49]),"=f"(d[50]),"=f"(d[51]),"=f"(d[52]),"=f"(d[53]),"=f"(d[54]),"=f"(d[55]),"=f"(d[56]),"=f"(d[57]),"=f"(d[58]),"=f"(d[59]),"=f"(d[60]),"=f"(d[61]),"=f"(d[62]),"=f"(d[63]),"=f"(d[64]),"=f"(d[65]),"=f"(d[66]),"=f"(d[67]),"=f"(d[68]),"=f"(d[69]),"=f"(d[70]),"=f"(d[71]),"=f"(d[72]),"=f"(d[73]),"=f"(d[74]),"=f"(d[75]),"=f"(d[76]),"=f"(d[77]),"=f"(d[78]),"=f"(d[79]),"=f"(d[80]),"=f"(d[81]),"=f"(d[82]),"=f"(d[83]),"=f"(d[84]),"=f"(d[85]),"=f"(d[86]),"=f"(d[87]),"=f"(d[88]),"=f"(d[89]),"=f"(d[90]),"=f"(d[91])
    : "l"(da), "l"(db));
}
DEVINL void wg_ss_n128(float (&d)[64], uint64_t da, uint64_t db, int sd) {
  asm volatile("{.reg .pred p; setp.ne.b32 p, %66, 0;\n"
    "wgmma.mma_async.sync.aligned.m64n128k16.f32.bf16.bf16 {%0,%1,%2,%3,%4,%5,%6,%7,%8,%9,%10,%11,%12,%13,%14,%15,%16,%17,%18,%19,%20,%21,%22,%23,%24,%25,%26,%27,%28,%29,%30,%31,%32,%33,%34,%35,%36,%37,%38,%39,%40,%41,%42,%43,%44,%45,%46,%47,%48,%49,%50,%51,%52,%53,%54,%55,%56,%57,%58,%59,%60,%61,%62,%63}, %64, %65, p, 1, 1, 0, 1;}\n"
    : "+f"(d[0]),"+f"(d[1]),"+f"(d[2]),"+f"(d[3]),"+f"(d[4]),"+f"(d[5]),"+f"(d[6]),"+f"(d[7]),"+f"(d[8]),"+f"(d[9]),"+f"(d[10]),"+f"(d[11]),"+f"(d[12]),"+f"(d[13]),"+f"(d[14]),"+f"(d[15]),"+f"(d[16]),"+f"(d[17]),"+f"(d[18]),"+f"(d[19]),"+f"(d[20]),"+f"(d[21]),"+f"(d[22]),"+f"(d[23]),"+f"(d[24]),"+f"(d[25]),"+f"(d[26]),"+f"(d[27]),"+f"(d[28]),"+f"(d[29]),"+f"(d[30]),"+f"(d[31]),"+f"(d[32]),"+f"(d[33]),"+f"(d[34]),"+f"(d[35]),"+f"(d[36]),"+f"(d[37]),"+f"(d[38]),"+f"(d[39]),"+f"(d[40]),"+f"(d[41]),"+f"(d[42]),"+f"(d[43]),"+f"(d[44]),"+f"(d[45]),"+f"(d[46]),"+f"(d[47]),"+f"(d[48]),"+f"(d[49]),"+f"(d[50]),"+f"(d[51]),"+f"(d[52]),"+f"(d[53]),"+f"(d[54]),"+f"(d[55]),"+f"(d[56]),"+f"(d[57]),"+f"(d[58]),"+f"(d[59]),"+f"(d[60]),"+f"(d[61]),"+f"(d[62]),"+f"(d[63])
    : "l"(da), "l"(db), "r"(sd));
}
DEVINL void wg_ss_n128_z(float (&d)[64], uint64_t da, uint64_t db) {
  asm volatile("{.reg .pred p; setp.ne.b32 p, 0, 0;\n"
    "wgmma.mma_async.sync.aligned.m64n128k16.f32.bf16.bf16 {%0,%1,%2,%3,%4,%5,%6,%7,%8,%9,%10,%11,%12,%13,%14,%15,%16,%17,%18,%19,%20,%21,%22,%23,%24,%25,%26,%27,%28,%29,%30,%31,%32,%33,%34,%35,%36,%37,%38,%39,%40,%41,%42,%43,%44,%45,%46,%47,%48,%49,%50,%51,%52,%53,%54,%55,%56,%57,%58,%59,%60,%61,%62,%63}, %64, %65, p, 1, 1, 0, 1;}\n"
    : "=f"(d[0]),"=f"(d[1]),"=f"(d[2]),"=f"(d[3]),"=f"(d[4]),"=f"(d[5]),"=f"(d[6]),"=f"(d[7]),"=f"(d[8]),"=f"(d[9]),"=f"(d[10]),"=f"(d[11]),"=f"(d[12]),"=f"(d[13]),"=f"(d[14]),"=f"(d[15]),"=f"(d[16]),"=f"(d[17]),"=f"(d[18]),"=f"(d[19]),"=f"(d[20]),"=f"(d[21]),"=f"(d[22]),"=f"(d[23]),"=f"(d[24]),"=f"(d[25]),"=f"(d[26]),"=f"(d[27]),"=f"(d[28]),"=f"(d[29]),"=f"(d[30]),"=f"(d[31]),"=f"(d[32]),"=f"(d[33]),"=f"(d[34]),"=f"(d[35]),"=f"(d[36]),"=f"(d[37]),"=f"(d[38]),"=f"(d[39]),"=f"(d[40]),"=f"(d[41]),"=f"(d[42]),"=f"(d[43]),"=f"(d[44]),"=f"(d[45]),"=f"(d[46]),"=f"(d[47]),"=f"(d[48]),"=f"(d[49]),"=f"(d[50]),"=f"(d[51]),"=f"(d[52]),"=f"(d[53]),"=f"(d[54]),"=f"(d[55]),"=f"(d[56]),"=f"(d[57]),"=f"(d[58]),"=f"(d[59]),"=f"(d[60]),"=f"(d[61]),"=f"(d[62]),"=f"(d[63])
    : "l"(da), "l"(db));
}
DEVINL void wg_ss_n32_ta(float (&d)[16], uint64_t da, uint64_t db, int sd) {
  asm volatile("{.reg .pred p; setp.ne.b32 p, %18, 0;\n"
    "wgmma.mma_async.sync.aligned.m64n32k16.f32.bf16.bf16 {%0,%1,%2,%3,%4,%5,%6,%7,%8,%9,%10,%11,%12,%13,%14,%15}, %16, %17, p, 1, 1, 1, 1;}\n"
    : "+f"(d[0]),"+f"(d[1]),"+f"(d[2]),"+f"(d[3]),"+f"(d[4]),"+f"(d[5]),"+f"(d[6]),"+f"(d[7]),"+f"(d[8]),"+f"(d[9]),"+f"(d[10]),"+f"(d[11]),"+f"(d[12]),"+f"(d[13]),"+f"(d[14]),"+f"(d[15])
    : "l"(da), "l"(db), "r"(sd));
}
DEVINL void wg_ss_n32_ta_z(float (&d)[16], uint64_t da, uint64_t db) {
  asm volatile("{.reg .pred p; setp.ne.b32 p, 0, 0;\n"
    "wgmma.mma_async.sync.aligned.m64n32k16.f32.bf16.bf16 {%0,%1,%2,%3,%4,%5,%6,%7,%8,%9,%10,%11,%12,%13,%14,%15}, %16, %17, p, 1, 1, 1, 1;}\n"
    : "=f"(d[0]),"=f"(d[1]),"=f"(d[2]),"=f"(d[3]),"=f"(d[4]),"=f"(d[5]),"=f"(d[6]),"=f"(d[7]),"=f"(d[8]),"=f"(d[9]),"=f"(d[10]),"=f"(d[11]),"=f"(d[12]),"=f"(d[13]),"=f"(d[14]),"=f"(d[15])
    : "l"(da), "l"(db));
}
DEVINL void wg_rs_n64(float (&d)[32], const uint32_t (&a)[4], uint64_t db, int sd) {
  asm volatile("{.reg .pred p; setp.ne.b32 p, %37, 0;\n"
    "wgmma.mma_async.sync.aligned.m64n64k16.f32.bf16.bf16 {%0,%1,%2,%3,%4,%5,%6,%7,%8,%9,%10,%11,%12,%13,%14,%15,%16,%17,%18,%19,%20,%21,%22,%23,%24,%25,%26,%27,%28,%29,%30,%31}, {%32,%33,%34,%35}, %36, p, 1, 1, 1;}\n"
    : "+f"(d[0]),"+f"(d[1]),"+f"(d[2]),"+f"(d[3]),"+f"(d[4]),"+f"(d[5]),"+f"(d[6]),"+f"(d[7]),"+f"(d[8]),"+f"(d[9]),"+f"(d[10]),"+f"(d[11]),"+f"(d[12]),"+f"(d[13]),"+f"(d[14]),"+f"(d[15]),"+f"(d[16]),"+f"(d[17]),"+f"(d[18]),"+f"(d[19]),"+f"(d[20]),"+f"(d[21]),"+f"(d[22]),"+f"(d[23]),"+f"(d[24]),"+f"(d[25]),"+f"(d[26]),"+f"(d[27]),"+f"(d[28]),"+f"(d[29]),"+f"(d[30]),"+f"(d[31])
    : "r"(a[0]), "r"(a[1]), "r"(a[2]), "r"(a[3]), "l"(db), "r"(sd));
}
DEVINL void wg_rs_n64_z(float (&d)[32], const uint32_t (&a)[4], uint64_t db) {
  asm volatile("{.reg .pred p; setp.ne.b32 p, 0, 0;\n"
    "wgmma.mma_async.sync.aligned.m64n64k16.f32.bf16.bf16 {%0,%1,%2,%3,%4,%5,%6,%7,%8,%9,%10,%11,%12,%13,%14,%15,%16,%17,%18,%19,%20,%21,%22,%23,%24,%25,%26,%27,%28,%29,%30,%31}, {%32,%33,%34,%35}, %36, p, 1, 1, 1;}\n"
    : "=f"(d[0]),"=f"(d[1]),"=f"(d[2]),"=f"(d[3]),"=f"(d[4]),"=f"(d[5]),"=f"(d[6]),"=f"(d[7]),"=f"(d[8]),"=f"(d[9]),"=f"(d[10]),"=f"(d[11]),"=f"(d[12]),"=f"(d[13]),"=f"(d[14]),"=f"(d[15]),"=f"(d[16]),"=f"(d[17]),"=f"(d[18]),"=f"(d[19]),"=f"(d[20]),"=f"(d[21]),"=f"(d[22]),"=f"(d[23]),"=f"(d[24]),"=f"(d[25]),"=f"(d[26]),"=f"(d[27]),"=f"(d[28]),"=f"(d[29]),"=f"(d[30]),"=f"(d[31])
    : "r"(a[0]), "r"(a[1]), "r"(a[2]), "r"(a[3]), "l"(db));
}
DEVINL void wg_rs_n32(float (&d)[16], const uint32_t (&a)[4], uint64_t db, int sd) {
  asm volatile("{.reg .pred p; setp.ne.b32 p, %21, 0;\n"
    "wgmma.mma_async.sync.aligned.m64n32k16.f32.bf16.bf16 {%0,%1,%2,%3,%4,%5,%6,%7,%8,%9,%10,%11,%12,%13,%14,%15}, {%16,%17,%18,%19}, %20, p, 1, 1, 1;}\n"
    : "+f"(d[0]),"+f"(d[1]),"+f"(d[2]),"+f"(d[3]),"+f"(d[4]),"+f"(d[5]),"+f"(d[6]),"+f"(d[7]),"+f"(d[8]),"+f"(d[9]),"+f"(d[10]),"+f"(d[11]),"+f"(d[12]),"+f"(d[13]),"+f"(d[14]),"+f"(d[15])
    : "r"(a[0]), "r"(a[1]), "r"(a[2]), "r"(a[3]), "l"(db), "r"(sd));
}
DEVINL void wg_rs_n32_z(float (&d)[16], const uint32_t (&a)[4], uint64_t db) {
  asm volatile("{.reg .pred p; setp.ne.b32 p, 0, 0;\n"
    "wgmma.mma_async.sync.aligned.m64n32k16.f32.bf16.bf16 {%0,%1,%2,%3,%4,%5,%6,%7,%8,%9,%10,%11,%12,%13,%14,%15}, {%16,%17,%18,%19}, %20, p, 1, 1, 1;}\n"
    : "=f"(d[0]),"=f"(d[1]),"=f"(d[2]),"=f"(d[3]),"=f"(d[4]),"=f"(d[5]),"=f"(d[6]),"=f"(d[7]),"=f"(d[8]),"=f"(d[9]),"=f"(d[10]),"=f"(d[11]),"=f"(d[12]),"=f"(d[13]),"=f"(d[14]),"=f"(d[15])
    : "r"(a[0]), "r"(a[1]), "r"(a[2]), "r"(a[3]), "l"(db));
}

struct Ring {
  int idx;
  uint32_t ph;
  DEVINL void adv() { if (++idx == NRING) { idx = 0; ph ^= 1; } }
};

template <int KIND> DEVINL void kstep(float (&d)[96], uint64_t da, uint32_t stage, int ks) {
  const uint64_t db = mkdesc(stage + ks * 2048, 4096, 1024, 1);
  if constexpr (KIND == 0) wg_ss_n184(*reinterpret_cast<float(*)[92]>(&d[0]), da, db, 1);
  else wg_ss_n192(d, da, db, 1);
}
template <int NR> DEVINL void acc_def(float (&d)[NR]) {
#pragma unroll
  for (int i = 0; i < NR; ++i) { d[i] = 0.f; asm volatile("" : "+f"(d[i])); }
}

template <int KIND, int SM_BAR, int NR, class MID, class TAIL>
DEVINL int gemm_in(float (&acc)[NR], uint32_t sb, int bo, int wg, int lane, Ring& r, uint32_t a_ph, int prev, MID mid, TAIL tail, uint32_t tl = 0) {
  auto step = [&](int it) {
    const int kb = it < 2 ? 6 : (it >> 1) - 1, hf = it & 1;
    TLST(tl && lane == 0, tl + 64 + it * 4, (uint32_t)clock());
    mbar_wait2(sb + SM_BAR + 8 * (B_AFULL + (it & 14) + wg), a_ph, sb + SM_BAR + 8 * (B_FULL + r.idx), r.ph);
    TLST(tl && lane == 0, tl + it * 4, (uint32_t)clock());
    const uint64_t da = mkdesc(sb + SM_A + kb * 16384 + wg * 8192 + hf * 64, 16, 1024, 1);
    wg_fence();
    kstep<KIND>(acc, da, sb + SM_RING + r.idx * STG + bo, 0);
    kstep<KIND>(acc, da + 2, sb + SM_RING + r.idx * STG + bo, 1);
    wg_commit();
    wg_wait<1>();
    if (lane == 0) mbar_arrive(sb + SM_BAR + 8 * (B_EMPTY + prev));
    prev = r.idx;
    r.adv();
  };
  if constexpr (KIND == 0) {
    mbar_wait2(sb + SM_BAR + 8 * (B_AFULL + wg), a_ph, sb + SM_BAR + 8 * (B_FULL + r.idx), r.ph);
    const uint64_t da = mkdesc(sb + SM_A + 6 * 16384 + wg * 8192, 16, 1024, 1);
    wg_fence();
    wg_ss_n184_z(*reinterpret_cast<float(*)[92]>(&acc[0]), da, mkdesc(sb + SM_RING + r.idx * STG + bo, 4096, 1024, 1));
    kstep<KIND>(acc, da + 2, sb + SM_RING + r.idx * STG + bo, 1);
    wg_commit();
    prev = r.idx;
    r.adv();
#pragma unroll 1
    for (int it = 1; it < CSI; ++it) step(it);
    mid();
  }
#pragma unroll 1
  for (int it = KIND ? 0 : CSI; it < 14; ++it) step(it);
  tail();
  if constexpr (KIND == 0) {
    wg_wait<0>();
    if (lane == 0) mbar_arrive(sb + SM_BAR + 8 * (B_EMPTY + prev));
  }
  return prev;
}

DEVINL void row_sums(const uint32_t (&a)[4], const uint32_t (&b)[4], float& lo, float& hi) {
  asm("{.reg .f32 x, y;\n"
      "mma.sync.aligned.m16n8k16.row.col.f32.bf16.bf16.f32 {%0,x,%1,y}, {%2,%3,%4,%5}, {%10,%10}, {%11,%11,%11,%11};\n"
      "mma.sync.aligned.m16n8k16.row.col.f32.bf16.bf16.f32 {%0,x,%1,y}, {%6,%7,%8,%9}, {%10,%10}, {%0,x,%1,y};}"
      : "=&f"(lo), "=&f"(hi)
      : "r"(a[0]), "r"(a[1]), "r"(a[2]), "r"(a[3]), "r"(b[0]), "r"(b[1]), "r"(b[2]), "r"(b[3]), "r"(0x3f803f80u), "f"(0.f));
}
DEVINL void softmax2(const float (&p)[2][16], float sc0, float sc1, uint32_t pm, uint32_t (&fr)[2][4][4]) {
  float v[2][16], mx[2][2], mn[2][2];
  auto range = [&](int h) {
#pragma unroll
    for (int i = 0; i < 16; ++i) v[h][i] = __fmul_rn(p[h][i], (i & 2) ? sc1 : sc0);
#pragma unroll
    for (int r = 0; r < 2; ++r) {
      const float* w = v[h] + 2 * r;
      mx[h][r] = fmaxf(fmaxf(fmaxf(w[0], w[1]), fmaxf(w[4], w[5])), fmaxf(fmaxf(w[8], w[9]), fmaxf(w[12], w[13])));
      mn[h][r] = fminf(fminf(fminf(w[0], w[1]), fminf(w[4], w[5])), fminf(fminf(w[8], w[9]), fminf(w[12], w[13])));
    }
#pragma unroll
    for (int m = 1; m < 3; ++m)
#pragma unroll
      for (int r = 0; r < 2; ++r) {
        mx[h][r] = fmaxf(mx[h][r], __shfl_xor_sync(~0u, mx[h][r], m));
        mn[h][r] = fminf(mn[h][r], __shfl_xor_sync(~0u, mn[h][r], m));
      }
  };
  auto full = [&](int h) {
#pragma unroll
    for (int i = 2 * h; i < 2 * h + 6; ++i) {
      const float e = ex2(__fsub_rn(v[h][2 * i], mx[h][i & 1]));
      if (i == 0) { sc0 = fmaf(e, 0.f, sc0); sc1 = fmaf(e, 0.f, sc1); }
      fr[h][i >> 2][i & 3] = pack2(e, ex2(__fsub_rn(v[h][2 * i + 1], mx[h][i & 1])));
    }
#pragma unroll
    for (int i = 2 * h; i < 2 * h + 6; ++i)
      fr[h][2 + (i >> 2)][i & 3] = pack2(ex2(__fsub_rn(mn[h][i & 1], v[h][2 * i])), ex2(__fsub_rn(mn[h][i & 1], v[h][2 * i + 1])));
  };
  auto norm = [&](int h) {
#pragma unroll
    for (int n = 0; n < 4; n += 2) {
      float lo, hi;
      row_sums(fr[h][n], fr[h][n + 1], lo, hi);
      const float r = rcp_fast(lo * hi);
      const uint32_t i2 = pack2(r * hi, r * lo);
#pragma unroll
      for (int i = 0; i < 8; ++i) fr[h][n + (i >> 2)][i & 3] = hmul2(fr[h][n + (i >> 2)][i & 3], __byte_perm(i2, 0u, i & 1 ? 0x3232 : 0x1010));
    }
  };
  range(0);
  full(0);
  range(1);
#pragma unroll
  for (int r = 0; r < 2; ++r) {
    const float x = pm ? v[0][12 + 2 * r] : v[1][2 * r], y = pm ? v[0][13 + 2 * r] : v[1][2 * r + 1];
    const float hi = pm ? mx[0][r] : mx[1][r], lo = pm ? mn[0][r] : mn[1][r];
    const uint32_t ep = pack2(ex2(__fsub_rn(x, hi)), ex2(__fsub_rn(y, hi))), en = pack2(ex2(__fsub_rn(lo, x)), ex2(__fsub_rn(lo, y)));
    fr[0][1][2 + r] = ep & pm;
    fr[0][3][2 + r] = en & pm;
    fr[1][0][r] = ep & ~pm;
    fr[1][2][r] = en & ~pm;
  }
  norm(0);
  full(1);
  norm(1);
}

template <bool SCALE>
DEVINL void qkv_frag(const float (&acc)[96], int sec, const float2 (&cs)[7], float m0, float r0, float m1, float r1,
                     uint32_t (&fr)[2][2][4]) {
#pragma unroll
  for (int i = 0; i < 7; ++i) {
    const float2 c = cs[i];
    const int o = sec * 32 + i * 4;
    const float a0 = fmaf(-m0, c.x, acc[o]), a1 = fmaf(-m0, c.y, acc[o + 1]), a2 = fmaf(-m1, c.x, acc[o + 2]), a3 = fmaf(-m1, c.y, acc[o + 3]);
    const uint32_t lo = SCALE ? pack2(a0 * r0, a1 * r0) : pack2(a0, a1), hi = SCALE ? pack2(a2 * r1, a3 * r1) : pack2(a2, a3);
    if (i < 4) { fr[0][i >> 1][(i & 1) * 2] = lo; fr[0][i >> 1][(i & 1) * 2 + 1] = hi; }
    if (i >= 3) { fr[1][(i - 3) >> 1][((i - 3) & 1) * 2] = lo; fr[1][(i - 3) >> 1][((i - 3) & 1) * 2 + 1] = hi; }
  }
}

struct LnRow { float m0, r0, m1, r1; };
DEVINL void glu_pre(float* g, float* u, const uint32_t (&c)[4], const LnRow& L) {
#pragma unroll
  for (int i = 0; i < 4; ++i) {
    g[i] = -(i < 2 ? L.m0 : L.m1) * __uint_as_float(c[i & 1]);
    u[i] = -(i < 2 ? L.m0 : L.m1) * __uint_as_float(c[2 + (i & 1)]);
    asm volatile("" : "+f"(g[i]), "+f"(u[i]));
  }
}
DEVINL void glu_post(const float* g, const float* u, const LnRow& L, uint32_t& h0, uint32_t& h1) {
  h0 = pack2(u[0] * fmaf(tanh_fast(g[0] * L.r0), L.r0, L.r0), u[1] * fmaf(tanh_fast(g[1] * L.r0), L.r0, L.r0));
  h1 = pack2(u[2] * fmaf(tanh_fast(g[2] * L.r1), L.r1, L.r1), u[3] * fmaf(tanh_fast(g[3] * L.r1), L.r1, L.r1));
}
DEVINL void glu_blk(const float* g, const float* u, const uint32_t (&c)[4], const LnRow& L, uint32_t& h0, uint32_t& h1) {
  const float cg0 = __uint_as_float(c[0]), cg1 = __uint_as_float(c[1]), cu0 = __uint_as_float(c[2]), cu1 = __uint_as_float(c[3]);
  const float g0 = tanh_fast(fmaf(-L.m0, cg0, g[0]) * L.r0), g1 = tanh_fast(fmaf(-L.m0, cg1, g[1]) * L.r0);
  const float g2 = tanh_fast(fmaf(-L.m1, cg0, g[2]) * L.r1), g3 = tanh_fast(fmaf(-L.m1, cg1, g[3]) * L.r1);
  const float u0 = fmaf(-L.m0, cu0, u[0]) * L.r0, u1 = fmaf(-L.m0, cu1, u[1]) * L.r0;
  const float u2 = fmaf(-L.m1, cu0, u[2]) * L.r1, u3 = fmaf(-L.m1, cu1, u[3]) * L.r1;
  h0 = pack2(fmaf(g0, u0, u0), fmaf(g1, u1, u1));
  h1 = pack2(fmaf(g2, u2, u2), fmaf(g3, u3, u3));
}

DEVINL void cs_part(const uint4 (&wv)[7], MemScratch& M, int u, int grp, int ln) {
  float f[8];
#pragma unroll
  for (int e = 0; e < 8; ++e) f[e] = 0.f;
#pragma unroll
  for (int i = 0; i < 7; ++i) {
    f[0] += bf_lo(wv[i].x); f[1] += bf_hi(wv[i].x); f[2] += bf_lo(wv[i].y); f[3] += bf_hi(wv[i].y);
    f[4] += bf_lo(wv[i].z); f[5] += bf_hi(wv[i].z); f[6] += bf_lo(wv[i].w); f[7] += bf_hi(wv[i].w);
  }
  const int rl = ln >> 3, c = ln & 7, uu = u < 3 ? u : u + 1;
#pragma unroll
  for (int e = 0; e < 4; ++e) {
    f[e] = (rl & 1 ? f[4 + e] : f[e]) + __shfl_xor_sync(~0u, rl & 1 ? f[e] : f[4 + e], 8);
    f[e] += __shfl_xor_sync(~0u, f[e], 16);
  }
  if (c < 7 && rl < 2)
    st_ll(M.cs + ((uu >> 1) * 16 + grp) * 32 + (uu & 1) * 14 + c * 2 + rl, __float_as_uint(f[0]), __float_as_uint(f[1]), __float_as_uint(f[2]),
          __float_as_uint(f[3]), 1u);
}
DEVINL void cs_load(uint4 (&v)[8], MemScratch& M, int u, int ln) {
  const int uu = u < 3 ? u : u + 1, l14 = ln & 15;
  const uint4* src = M.cs + (uu >> 1) * 512 + (ln >> 4) * 256 + (uu & 1) * 14 + (l14 < 14 ? l14 : 0);
  static_for<0, 8>([&](auto I) { v[I.value] = ld_ll_o<I.value * 512>(src); });
}
DEVINL void cs_total(uint4 (&v)[8], MemScratch& M, int u, int ln, int par, uint32_t sb, uint32_t bar) {
  int n = 0;
  while (__any_sync(~0u, (chk4(v, 1u) | chk4(v + 4, 1u)) & 1u)) {
    cs_load(v, M, u, ln);
    SPIN_GUARD(n);
  }
  float4 acc = make_float4(0.f, 0.f, 0.f, 0.f);
#pragma unroll
  for (int s = 0; s < 8; ++s) {
    acc.x += __uint_as_float(v[s].x); acc.y += __uint_as_float(v[s].y);
    acc.z += __uint_as_float(v[s].z); acc.w += __uint_as_float(v[s].w);
  }
  acc.x += __shfl_xor_sync(~0u, acc.x, 16); acc.y += __shfl_xor_sync(~0u, acc.y, 16);
  acc.z += __shfl_xor_sync(~0u, acc.z, 16); acc.w += __shfl_xor_sync(~0u, acc.w, 16);
  int k = ((u - 3) & 3) * 14 + ln - 8 * par;
  if (k < 0) k += 56;
  const uint32_t da = sb + SM_CS + (u < 3 ? u * 256 + 16 * ln : 768 + 8 * ((u - 3) >> 2) + 32 * k);
  if (ln < 14) {
    asm volatile("st.shared.v2.f32 [%0], {%1,%2};" ::"r"(da), "f"(acc.x), "f"(acc.y) : "memory");
    asm volatile("st.shared.v2.f32 [%0], {%1,%2};" ::"r"(da + (u < 3 ? 8 : 16)), "f"(acc.z), "f"(acc.w) : "memory");
  }
  __syncwarp();
  if (ln == 0) mbar_arrive(bar);
}

template <bool two, bool safe, int ROLE = -1>
DEVINL void run(const Ptrs& Q, const Params& P, const uint32_t sb, const int tid, const int bid) {
  constexpr int SM_BAR = SM_BAR0 + (safe ? 448 : 0);
  const int warp = __shfl_sync(~0u, tid >> 5, 0), lane = tid & 31;
  const int par = bid & 1, grp = (bid >> 1) & 15, p = 2 * (bid >> 5) + par;
  auto BAR = [&](int i) { return sb + SM_BAR + 8 * i; };
  GrpScratch& G = Q.S->grp[grp];
  MemScratch& M = Q.S->mem[p];

  uint4 wv[7];
  auto load_wv = [&] {
    const __nv_bfloat16* w = Q.wqkv + (28 * grp + 7 * (lane >> 3)) * 1344 + 448 * (warp < 11 ? warp - 8 : 0) + 56 * p + 8 * ((lane & 7) < 7 ? lane & 7 : 0);
#pragma unroll
    for (int i = 0; i < 7; ++i) wv[i] = ld_nc16(w + i * 1344);
    TL(44);
  };
  if (ROLE < 0 ? warp < 12 : ROLE < 2) cluster_arrive();
  auto exchange = [&](int st, int i, int lane) {
    const uint32_t slot = sb + SM_A + i * 32768;
    const bool sure = safe || (st == 3 && i == 3);
    uint32_t* const tk = Q.S->tick + opaque(64 * (grp * 4 + i));
    uint32_t* const fl = sure ? G.done[i] + opaque(0) : tk + 32 * par;
    uint32_t seq = sure ? ld_flag(fl + p) : ld_flag(fl) | 7;
    int n = 0;
    auto meet = [&](auto S) {
      __syncwarp();
      TLW(14, 16 + st * 4 + i);
      if constexpr (S.value) { while (__any_sync(~0u, ld_acquire(fl + (lane & 7)) == seq)) SPIN_GUARD(n); }
      else { while (__any_sync(~0u, ld_flag(fl) != seq + 1)) SPIN_GUARD(n); }
    };
    const CUtensorMap* const to = &P.m_o64 + sure;
    const int c0 = 128 * i + 64 * (i < 3 && par), wd = (st & 1) || i == 3 ? 0 : i == 0 ? WD1 : i == 1 ? WD2 : WD3;
    const uint32_t src = slot + 16384 * (i < 3 && par);
    auto add = [&](int hf) {
      tma_add1(to, c0, grp * 128 + 64 * hf, src + 8192 * hf);
      if (!safe) count1(tk + 32 * hf, sb + SM_BAR0 + 448);
    };
    mbar_wait2(BAR(B_STAGED + i), st & 1, BAR((st & 1 ? B_STAGED : B_STAGED1) + i), st & 1);
    if (wd) short_wait(wd);
    add(0);
    bulk_read();
    if (wd) short_wait(WDH);
    mbar_wait(BAR(B_STAGED1 + i), st & 1);
    add(1);
    bulk_done();
    TLW(14, st * 4 + i);
    if (!sure && lane == 0) mbar_arrive(BAR(B_ADDED));
    if (i == 0 && lane < 14) mbar_expect(BAR(B_AFULL + lane), 8192);
    if (sure) {
      if (elect_one()) st_release(fl + p, seq + 1);
      meet(IC<1>{});
      ++seq;
      asm volatile("fence.proxy.async.global;" ::: "memory");
      const int o = (grp * 128 + 16 * p + (lane >> 3)) * DM + 128 * i + 8 * (lane & 7);
#pragma unroll 1
      for (int e = 0; e < (i < 3 ? 4 : 2); ++e) {
        __nv_bfloat16 *const pu = Q.S->upd + o + (e & 1) * 8 * DM + (e >> 1) * 64, *const px = Q.out + (pu - Q.S->upd);
        const uint4 u0 = ld_ll_o<0>(pu), x0 = ld_ll_o<0>(px), u1 = ld_ll_o<8 * DM>(pu), x1 = ld_ll_o<8 * DM>(px);
        *(uint4*)px = make_uint4(hadd2(x0.x, u0.x), hadd2(x0.y, u0.y), hadd2(x0.z, u0.z), hadd2(x0.w, u0.w));
        *(uint4*)(px + 4 * DM) = make_uint4(hadd2(x1.x, u1.x), hadd2(x1.y, u1.y), hadd2(x1.z, u1.z), hadd2(x1.w, u1.w));
        *(uint4*)pu = *(uint4*)(pu + 4 * DM) = make_uint4(0u, 0u, 0u, 0u);
      }
      TLW(14, 30);
      if constexpr (safe) {
        asm volatile("fence.proxy.async.global;" ::: "memory");
        __syncwarp();
        if (st < 3 && elect_one()) st_release(fl + p, seq + 1);
      }
    }
    if (st == 3) return;
    meet(IC<safe>{});
    if (!safe) short_wait((st & 1 ? i == 2 : i % 3 == 0) ? TK_D * 5 / 6 : TK_D);
    const uint32_t bar = BAR(B_AFULL + (i < 3 ? 4 * i + 2 : 0) + par);
    tma4d_mc1(slot + par * 8192, &P.m_o64, 128 * i, grp * 128 + par * 64, bar);
    if (i < 3) tma4d_mc1(slot + 16384 + par * 8192, &P.m_o64, 128 * i + 64, grp * 128 + par * 64, bar + 16);
    TLW(13, st * 16 + 16 + i);
  };

  if (ROLE < 0 ? warp < 8 : ROLE == 0) {
    TL(61);
    asm volatile("setmaxnreg.inc.sync.aligned.u32 208;");
    TL(62);
    bar_sync(5, 384);
    const int tid = my_tid(), lane = tid & 31;
    Ring r{0, 0};
#pragma unroll 1
    for (int st = 0; st < 4; ++st) {
      const int wx = __shfl_sync(~0u, (tid >> 5) + 8 * bid, 0), warp = wx & 7, wg = warp >> 2, w = warp & 3, t = lane & 3;
      const int par = (wx >> 3) & 1, grp = (wx >> 4) & 15;
      MemScratch& M = Q.S->mem[2 * (wx >> 8) + par];
      const uint32_t peer = mapa(sb, par ^ 1);
      const uint32_t cs_t = sb + SM_CS + t * 8;
      const int sm_hi = lane >> 4;
      const int sm_off = warp * 2048 + (lane & 15) * 128 + ((sm_hi ^ (lane & 7)) << 4);
      const int row_lo = warp * 16 + (lane >> 2);
      const uint32_t hl_off = SM_A + 2 * 16384 + warp * 2048 + lane * 16;
      auto HL = [&](int ks) { return hl_off + (ks >> 2) * 16384 + (ks & 3) * 512; };
      uint32_t h[14][4];
      auto stage_out = [&](const float (&a)[32], int i) {
        const uint32_t stg = sb + SM_A + (2 * i + (i < 3 ? par : 0)) * 16384 + opaque(sm_off);
#pragma unroll
        for (int s = 0; s < 4; ++s)
          stmat4(stg ^ (s * 32), pack2(a[8 * s], a[8 * s + 1]), pack2(a[8 * s + 2], a[8 * s + 3]),
                 pack2(a[8 * s + 4], a[8 * s + 5]), pack2(a[8 * s + 6], a[8 * s + 7]));
        fence_async();
        __syncwarp();
        if (lane == 0) mbar_arrive(BAR(B_STAGED + i + wg * (B_STAGED1 - B_STAGED)));
        TL(32 + st * 4 + i);
      };
      int prev = 0;
      [[maybe_unused]] int tlc = 0;
      auto take = [&] {
        mbar_wait(BAR(B_FULL + r.idx), r.ph);
        TLG3();
        const uint64_t db = mkdesc(sb + SM_RING + r.idx * STG, 16, 1024, 1);
        r.adv();
        return db;
      };
      auto give = [&] {
        if (lane == 0) mbar_arrive(BAR(B_EMPTY + prev));
        prev = prev == NRING - 1 ? 0 : prev + 1;
      };
      if ((tid & 127) == 0) {
        mbar_expect(BAR(B_STATF + wg), 512);
        mbar_expect(BAR(B_HX0 + wg), 8192);
        if (st & 1) mbar_expect(BAR(B_HX1 + wg), 20480);
      }
      if (__shfl_sync(~0u, ~st, 0) & 1) {
        float acc[96];
        TL(st * 8 + 0);
        float2 s0, s1, cs[7];
        auto sums = [&](int sec) {
#pragma unroll
          for (int i = 0; i < 7; ++i) cs[i] = lds8(cs_t + (sec * 64 + i * 8) * 4);
        };
        uint4 cv[8];
#pragma unroll
        for (int i = 0; i < 8; ++i) cv[i] = make_uint4(0u, 0u, 0u, 0u);
        const int cu = st ? 3 : (warp - 5) & 7;
        gemm_in<0, SM_BAR>(acc, sb, 16 * par, wg, lane, r, 0, 0, [&] {
          if (cu < 3) cs_load(cv, M, cu, opaque(lane));
        }, [&] {
          TL(48 + st);
          if (cu < 3) cs_total(cv, M, cu, opaque(lane), par, sb, BAR(cu ? B_CSF : B_CSQ));
          if (st == 0) {
            cluster_wait();
            uint4* dst = M.kv1 + (warp * 32 + grp) * 32 + opaque(lane);
            st_ll_o<0>(dst, 0u, 0u, 0u, 0u, 0u);
            st_ll_o<8192>(dst, 0u, 0u, 0u, 0u, 0u);
          }
          mbar_wait2(BAR(B_STATF + wg), 0, BAR(B_CSF), 0);
          TL(52 + st);
          s0 = lds8(sb + SM_STATS + row_lo * 8);
          s1 = lds8(sb + SM_STATS + (row_lo + 8) * 8);
          sums(1);
        } TLARG(st == TLG - 1, 12, 0));
        TL(st * 8 + 1);
        const uint32_t kvtag = (st >> 1) ^ 1;
        uint32_t fin[2][2][4], fr[2][4][4];
        qkv_frag<false>(acc, 1, cs, s0.x, s0.y, s1.x, s1.y, fin);
#pragma unroll 1
        for (int z = 0; z < 2; ++z) {
          float pk[2][16];
          {
            const uint64_t db = mkdesc(sb + SM_WPHI, 16, 512, 2);
            wg_fence();
            wg_rs_n32_z(pk[0], fin[0][0], db);
            wg_rs_n32(pk[0], fin[0][1], db + 64, 1);
            wg_rs_n32_z(pk[1], fin[1][0], db + 128);
            wg_rs_n32(pk[1], fin[1][1], db + 192, 1);
            wg_commit();
            if (st == 2) TL(56 + 4 * z);
          }
          auto put_v = [&] {
            uint32_t fv[2][2][4];
            sums(2);
            qkv_frag<true>(acc, 2, cs, s0.x, s0.y, s1.x, s1.y, fv);
            uint32_t (&f0)[2][4] = fv[0];
            uint32_t (&f1)[2][4] = fv[1];
            if (t >= 2) f0[1][2] = f0[1][3] = (t == 2) ? 0x00003f80u : 0u;
            if (t < 2) f1[0][0] = f1[0][1] = (t == 0) ? 0x00003f80u : 0u;
            const uint32_t vb = sb + SM_A + (4 + par) * 16384 + opaque(sm_off);
#pragma unroll
            for (int s = 0; s < 2; ++s) {
              stmat4(vb ^ (s * 32), f0[s][0], f0[s][1], f0[s][2], f0[s][3]);
              stmat4(vb ^ (64 + s * 32), f1[s][0], f1[s][1], f1[s][2], f1[s][3]);
            }
          };
          if (z == 0 && wg) put_v();
          if (st == 2 && z == 0) TL(57);
          wg_wait<0>();
          if (st == 2) TL(58 + 5 * z);
          softmax2(pk, s0.y * 1.4426950408889634f, s1.y * 1.4426950408889634f, t < 2 ? ~0u : 0u, fr);
          if (z == 0) {
            const uint32_t pb = sb + SM_A + par * 16384 + opaque(sm_off);
#pragma unroll
            for (int hh = 0; hh < 2; ++hh) {
#pragma unroll
              for (int s = 0; s < 4; ++s) stmat4((pb ^ (s * 32)) + hh * 32768, fr[hh][s][0], fr[hh][s][1], fr[hh][s][2], fr[hh][s][3]);
            }
            if (!wg) put_v();
            if (st == 2) TL(59);
            fence_async();
            if (st == 2) TL(12);
            bar_sync(1, 256);
            TL(st * 8 + 2);
            float kv[16];
            const uint64_t da = mkdesc(sb + SM_A + (2 * wg + par) * 16384, 16, 1024, 1), db = mkdesc(sb + SM_A + (4 + par) * 16384 + wg * 64, 16, 1024, 1);
            wg_fence();
            wg_ss_n32_ta_z(kv, da, db);
#pragma unroll
            for (int ks = 1; ks < 8; ++ks) wg_ss_n32_ta(kv, da + ks * 128, db + ks * 128, 1);
            wg_commit();
            wg_wait<0>();
            if (st == 2) TL(13);
            uint4* dst = M.kv1 + ((wg * 8 + w * 2) * 16 + grp) * 32 + opaque(lane);
            static_for<0, 2>([&](auto I) {
              constexpr int o = I.value * 2;
              st_ll_o<I.value * 8192>(dst, pack_tag(kv[o], kv[o + 1], kvtag), pack2(kv[o + 4], kv[o + 5]), pack_tag(kv[o + 8], kv[o + 9], kvtag),
                                      pack2(kv[o + 12], kv[o + 13]), kvtag);
            });
            __syncwarp();
            if (lane == 0) {
              mbar_arrive(BAR(B_KVSENT));
              mbar_arrive_remote(peer + SM_BAR + 8 * (B_AFREE + wg));
            }
            TL(st * 8 + 3);
            mbar_wait(BAR(B_CSQ), 0);
            sums(0);
            qkv_frag<false>(acc, 0, cs, s0.x, s0.y, s1.x, s1.y, fin);
          }
        }
        TL(st * 8 + 4);
        {
          const uint4* src = M.kv2 + warp * 64 + opaque(lane);
          uint4 lo = ld_ll_o<0>(src), hi = ld_ll_o<512>(src);
          mbar_wait2(BAR(B_AFREE), 0, BAR(B_AFREE + 1), 0);
          mbar_wait(BAR(B_WO), st >> 1);
          int n = 0;
          while (__any_sync(~0u, (tagchk(lo.x, lo.z, kvtag) | tagchk(hi.x, hi.z, kvtag)) & 1u)) {
            lo = ld_ll_o<0>(src);
            hi = ld_ll_o<512>(src);
            SPIN_GUARD(n);
          }
          const int frw = w * 16 + (opaque(lane) & 15);
          const uint32_t kb = sb + SM_KVB + wg * 4096 + frw * 64 + ((sm_hi ^ ((frw >> 1) & 3)) << 4);
          stmat4(kb, lo.x, hi.x, lo.y, hi.y);
          stmat4(kb ^ 32, lo.z, hi.z, lo.w, hi.w);
          fence_async();
          bar_sync(1, 256);
        }
        TL(st * 8 + 5);
        float o0[16], o1[16];
        {
          const uint64_t db = mkdesc(sb + SM_KVB, 16, 512, 2);
          wg_fence();
          wg_rs_n32_z(o0, fr[0][0], db);
#pragma unroll
          for (int ks = 1; ks < 4; ++ks) wg_rs_n32(o0, fr[0][ks], db + ks * 64, 1);
          wg_rs_n32_z(o1, fr[1][0], db + 256);
#pragma unroll
          for (int ks = 1; ks < 4; ++ks) wg_rs_n32(o1, fr[1][ks], db + 256 + ks * 64, 1);
          wg_commit();
          wg_wait<0>();
        }
        const float d00 = rcp_fast(__shfl_sync(~0u, o0[12], (lane & ~3) | 2) + 1e-6f);
        const float d01 = rcp_fast(__shfl_sync(~0u, o0[14], (lane & ~3) | 2) + 1e-6f);
        const float d10 = rcp_fast(__shfl_sync(~0u, o1[0], lane & ~3) + 1e-6f);
        const float d11 = rcp_fast(__shfl_sync(~0u, o1[2], lane & ~3) + 1e-6f);
#pragma unroll
        for (int i = 0; i < 4; ++i) {
          h[i >> 1][(i & 1) * 2 + 0] = pack2(o0[4 * i] * d00, o0[4 * i + 1] * d00);
          h[i >> 1][(i & 1) * 2 + 1] = pack2(o0[4 * i + 2] * d01, o0[4 * i + 3] * d01);
          h[2 + (i >> 1)][(i & 1) * 2 + 0] = pack2(o1[4 * i] * d10, o1[4 * i + 1] * d10);
          h[2 + (i >> 1)][(i & 1) * 2 + 1] = pack2(o1[4 * i + 2] * d11, o1[4 * i + 3] * d11);
        }
        if (t >= 2) h[1][2] = h[1][3] = 0u;
        if (t < 2) h[2][0] = h[2][1] = 0u;
        TL(st * 8 + 6);
#pragma unroll
        for (int ks = 0; ks < 4; ++ks) st_async16(peer + HL(12 + ks) - par * 16384, h[ks], peer + SM_BAR + 8 * (B_HX0 + wg));
        float a[4][32];
        const uint64_t db = mkdesc(sb + SM_A + (par ^ 1) * 16384, 16, 1024, 1), dh = mkdesc(sb + SM_RING + 12288, 16, 1024, 1);
        auto mm = [&](auto I, auto K0) {
          constexpr int i = I.value, k0 = K0.value;
          const int o = k0 ? par ^ 1 : par;
#pragma unroll
          for (int ks = 0; ks < 4; ++ks) {
            const uint64_t d = i < 3 ? db + i * 2048 + o * 512 + ks * 128 : dh + (ks >> 1) * 1024 + (ks & 1) * 128;
            if (k0 + ks == 0) wg_rs_n64_z(a[i], h[0], d);
            else wg_rs_n64(a[i], h[k0 + ks], d, 1);
          }
        };
        wg_fence();
        mm(IC<3>{}, IC<0>{});
        wg_commit();
        wg_wait<0>();
        stage_out(a[3], 3);
        wg_fence();
        mm(IC<0>{}, IC<0>{});
        if (WOA > 1) mm(IC<1>{}, IC<0>{});
        wg_commit();
        mbar_wait(BAR(B_HX0 + wg), 0);
#pragma unroll
        for (int ks = 0; ks < 4; ++ks) lds16(sb + HL(8 + ks) + par * 16384, h[4 + ks]);
        wg_fence();
        mm(IC<0>{}, IC<4>{});
        wg_commit();
        wg_wait<0>();
        stage_out(a[0], 0);
        wg_fence();
        if (WOA < 2) mm(IC<1>{}, IC<0>{});
        mm(IC<1>{}, IC<4>{});
        wg_commit();
        mm(IC<2>{}, IC<0>{});
        wg_commit();
        wg_wait<1>();
        stage_out(a[1], 1);
        wg_fence();
        mm(IC<2>{}, IC<4>{});
        wg_commit();
        wg_wait<0>();
        stage_out(a[2], 2);
      } else {
        TL(st * 8 + 0);
        float acc[96], ac2[64], ac3[64];
        const uint32_t csb = sb + SM_CS + 768 + t * 16;
        uint32_t cc[2][4];
        acc_def(acc);
        LnRow L;
        uint32_t aad = sb + SM_A + 6 * 16384 + wg * 8192;
        auto issue = [&](float (&d)[64], auto first) {
          mbar_wait(BAR(B_FULL + r.idx), r.ph);
          TLG3();
          const uint64_t da = mkdesc(aad, 16, 1024, 1), db = mkdesc(sb + SM_RING + r.idx * STG, 8192, 1024, 1);
          wg_fence();
          if constexpr (first.value) wg_ss_n128_z(d, da, db);
          else wg_ss_n128(d, da, db, 1);
#pragma unroll
          for (int ks = 1; ks < 4; ++ks) wg_ss_n128(d, da + 2 * ks, db + 128 * ks, 1);
          wg_commit();
          aad += 16384;
        };
        auto release = [&] {
          wg_wait<1>();
          if (lane == 0) mbar_arrive(BAR(B_EMPTY + prev));
        };
        auto next = [&] { prev = r.idx; r.adv(); };
        mbar_wait(BAR(B_AFULL + wg), 1);
        issue(ac2, IC<1>{});
        next();
        aad -= 7 * 16384;
        auto stats = [&] {
          TL(48 + st);
          mbar_wait2(BAR(B_STATF + wg), 1, BAR(B_CSG), 0);
          TL(52 + st);
          const float2 s0 = lds8(sb + SM_STATS + row_lo * 8), s1 = lds8(sb + SM_STATS + (row_lo + 8) * 8);
          L = LnRow{s0.x, 0.5f * s0.y, s1.x, 0.5f * s1.y};
          lds16(csb + 24 * 64, cc[0]);
          lds16(csb + 25 * 64, cc[1]);
        };
        prev = gemm_in<1, SM_BAR>(acc, sb, 0, wg, lane, r, 1, prev, [] {}, stats TLARG(st == TLG, 15, 16));
        TL(st * 8 + 1);
        TL(st * 8 + 2);
        auto slice = [&](const float* src, uint32_t (&hh)[4], int nx, int du = 32, bool rel = true) {
          glu_blk(src, src + du, cc[0], L, hh[0], hh[1]);
          if (rel) release();
          if (nx != 8) lds16(csb + nx * 64, cc[0]);
          glu_blk(src + 4, src + 4 + du, cc[1], L, hh[2], hh[3]);
          if (nx != 8) lds16(csb + nx * 64 + 64, cc[1]);
        };
        auto park = [&](int i) { sts16(sb + SM_KVB + i * 4096 + tid * 16, make_uint4(h[12 + i][0], h[12 + i][1], h[12 + i][2], h[12 + i][3])); };
        static_for<0, 6>([&](auto J) {
          constexpr int j = J.value;
          issue(ac2, IC<0>{});
          if constexpr (j == 0) {
            release();
            slice(acc + 64, h[12], 26, 16, false);
            park(0);
          } else if constexpr (j == 1) {
            slice(acc + 72, h[13], 16, 16);
            park(1);
          } else {
            uint32_t ci[2][4];
            lds16(csb + (4 + 2 * j) * 64, ci[0]);
            lds16(csb + (5 + 2 * j) * 64, ci[1]);
            slice(acc + 8 * j - 16, h[6 + j], j < 5 ? 14 + 2 * j : 0);
            glu_pre(ac3 + 8 * j - 16, ac3 + 8 * j + 16, ci[0], L);
            glu_pre(ac3 + 8 * j - 12, ac3 + 8 * j + 20, ci[1], L);
          }
          next();
        });
        aad -= 4 * 16384;
        auto at = [&](int ks) { return HL(ks < 4 ? ks + 4 : ks < 8 ? ks + 6 : ks < 12 ? ks - 8 : ks - 4); };
        auto send = [&](int ks) { st_async16(peer + at(ks), h[ks], peer + SM_BAR + 8 * ((ks & 12) == 4 ? B_HX0 + wg : B_HX1 + wg)); };
        auto recv = [&](int ks, uint32_t (&f)[4]) { lds16(sb + at(ks), f); };
        static_for<0, 7>([&](auto J) {
          constexpr int j = J.value;
          if constexpr (j == YJ) if (YW && wg) short_wait(YW);
          issue(ac3, IC<0>{});
          if constexpr (j == 4) aad -= 7 * 16384;
          if constexpr (j >= 1 && j < 5) slice(ac2 + 8 * j - 8, h[j - 1], 2 * j);
          if constexpr (j == 5) { lds16(sb + SM_KVB + tid * 16, h[12]); lds16(sb + SM_KVB + 4096 + tid * 16, h[13]); }
          if constexpr (j == 2 || j == 4)
            if (lane == 0) mbar_arrive_remote(peer + SM_BAR + 8 * ((j == 2 ? B_AFREE2 : B_AFREE) + wg));
          if constexpr (j == 3) mbar_wait(BAR(B_AFREE2 + wg), st >> 1);
          if constexpr (j == 6) mbar_wait(BAR(B_AFREE + wg), 1);
          if constexpr (j >= 3) {
#pragma unroll
            for (int e = (j == 3 ? 0 : 3 * j - 10); e < (j == 6 ? 10 : 3 * j - 7); ++e) send(e < 4 ? e + 8 : e < 8 ? e - 4 : e + 4);
          }
          if constexpr (j == 0 || j >= 5) release();
          next();
        });
        uint32_t hp[14][4];
        float a0[32], a1[32];
        auto mm = [&](float (&a)[32], const uint32_t (&fr)[14][4], uint64_t db, auto K0, auto K1, auto Z) {
          wg_fence();
#pragma unroll
          for (int ks = K0.value; ks < K1.value; ++ks) {
            if (Z.value == 1 && ks == K0.value) wg_rs_n64_z(a, fr[ks], db + (ks & 7) * 128);
            else wg_rs_n64(a, fr[ks], db + (ks & 7) * 128, Z.value != 2 || ks != K0.value);
          }
          wg_commit();
        };
        auto last = [&](auto S) {
          constexpr int s = S.value;
          glu_post(ac3 + 8 * s, ac3 + 32 + 8 * s, L, h[4 + s][0], h[4 + s][1]);
          glu_post(ac3 + 8 * s + 4, ac3 + 36 + 8 * s, L, h[4 + s][2], h[4 + s][3]);
          send(4 + s);
        };
        auto full = [&](float (&a)[32], const uint32_t (&fr)[14][4], auto K0) {
          mm(a, fr, take(), K0, IC<K0.value ? 14 : 8>{}, IC<0>{});
          wg_wait<1>();
          give();
        };
        auto turn = [&](float (&an)[32], auto Z, auto out) {
          const uint64_t db = take();
          mm(an, h, db, IC<8>{}, IC<8 + NT>{}, Z);
          wg_wait<1>();
          give();
          out();
          mm(an, h, db, IC<8 + NT>{}, IC<14>{}, IC<0>{});
        };
        {
          const uint64_t d0 = take();
          mm(a0, h, d0, IC<8>{}, IC<11>{}, IC<1>{});
          wg_wait<1>();
          give();
          TL(st * 8 + 3);
          last(IC<0>{});
          mm(a0, h, d0, IC<11>{}, IC<14>{}, IC<0>{});
          last(IC<1>{});
          const uint64_t d1 = take();
          mm(a0, h, d1, IC<0>{}, IC<2>{}, IC<0>{});
          last(IC<2>{});
          mm(a0, h, d1, IC<2>{}, IC<4>{}, IC<0>{});
          wg_wait<1>();
          give();
          last(IC<3>{});
          TL(st * 8 + 6);
          mm(a0, h, d1, IC<4>{}, IC<8>{}, IC<0>{});
        }
        auto recv1 = [&] {
          mbar_wait(BAR(B_HX1 + wg), st >> 1);
#pragma unroll
          for (int ks = 8; ks < 18; ++ks) recv(ks % 14, hp[ks % 14]);
        };
        auto recv0 = [&] {
          mbar_wait(BAR(B_HX0 + wg), 1);
#pragma unroll
          for (int ks = 4; ks < 8; ++ks) recv(ks, hp[ks]);
        };
        turn(a1, IC<1>{}, [&] { stage_out(a0, 3); recv1(); });
        full(a1, h, IC<0>{});
        recv0();
        full(a1, hp, IC<8>{});
        full(a1, hp, IC<0>{});
        turn(a0, IC<2>{}, [&] { stage_out(a1, 0); });
        full(a0, h, IC<0>{});
        full(a0, hp, IC<8>{});
        full(a0, hp, IC<0>{});
        turn(a1, IC<2>{}, [&] { stage_out(a0, 1); });
        full(a1, h, IC<0>{});
        full(a1, hp, IC<8>{});
        full(a1, hp, IC<0>{});
        wg_wait<0>();
        give();
        stage_out(a1, 2);
      }
      TL(st * 8 + 7);
    }
  } else if (ROLE < 0 ? warp < 12 : ROLE == 1) {
    asm volatile("setmaxnreg.dec.sync.aligned.u32 56;");
    const int q = warp - 8, lane = my_tid() & 31;
    load_wv();
#pragma unroll 1
    for (int st = -1; st < 4; ++st) {
      int ln = lane;
      asm volatile("" : "+r"(ln));
      const int rl = ln >> 3, c = ln & 7;
      if (st <= 0) {
        if (st == 0 && ln < 16) st_ll8((uint2*)(M.kv2 + grp * 32) + q * 16 + ln, 0u, 0u, 0u);
#pragma unroll 1
        for (int u = q + 3 * (st + 1); u < 11 + 8 * st; u += 4) {
          if (st == 0) {
            const __nv_bfloat16* s = (u < 7 ? Q.wg : Q.wu) + 56 * (grp * (FF / 2) + 4 * p + ((u - 3) & 3)) + opaque(7 * FF * rl + 8 * (c < 7 ? c : 0));
#pragma unroll
            for (int i = 0; i < 7; ++i) wv[i] = ld_nc16(s + i * FF);
          }
          cs_part(wv, M, u, grp, ln);
        }
        TL(41 + st);
        if (st < 0) bar_sync(4, 256);
      }
      if (st == 3) {
#pragma unroll 1
        for (int i = q; i < 6; i += 4) st_ll(M.cs + (i * 16 + grp) * 32 + ln, 0u, 0u, 0u, 0u, 0u);
        st_flag(M.pk + grp + (ln & 16), 0u);
      }
      if ((st & 1) == 0) {
        const uint32_t ktag = (st >> 1) ^ 1;
        const uint32_t one = ln & 4 ? 0x3f800000u : 0x3f80u, b0 = opaque(ln & 8 ? 0u : one), b1 = opaque(one ^ b0);
        mbar_wait(BAR(B_KVSENT), st >> 1);
        short_wait(KV1_D);
        TL(st * 8 + 6);
        const uint4* src = M.kv1 + (grp * 16 + (ln & 3)) * 32 + q * 8 + (ln >> 2);
        uint4 v[4];
#pragma unroll
        for (int i = 0; i < 4; ++i) v[i] = make_uint4(~ktag, 0u, 0u, 0u);
        int n = 0;
        while (true) {
          static_for<0, 4>([&](auto I) { ld_ll_miss<I.value * 2048>(v[I.value], src, ktag); });
          if (!__any_sync(~0u, chk4(v, ktag) & 1u)) break;
          SPIN_GUARD(n);
        }
        TL(st * 8 + 4);
        TLV(st * 8 + 5, n);
        float f[2][4];
#pragma unroll
        for (int i = 0; i < 4; ++i) {
          float (&d)[4] = f[i & 1];
          if (i < 2) d[0] = d[1] = d[2] = d[3] = 0.f;
          asm("mma.sync.aligned.m16n8k16.row.col.f32.bf16.bf16.f32 {%0,%1,%2,%3}, {%4,%5,%6,%7}, {%8,%9}, {%0,%1,%2,%3};"
              : "+f"(d[0]), "+f"(d[1]), "+f"(d[2]), "+f"(d[3]) : "r"(v[i].x), "r"(v[i].y), "r"(v[i].z), "r"(v[i].w), "r"(b0), "r"(b1));
        }
        st_ll8((uint2*)(M.kv2 + grp * 32) + q * 16 + (ln >> 2) * 2 + (ln & 1), pack_tag(f[0][0] + f[1][0], f[0][1] + f[1][1], ktag),
               pack2(f[0][2] + f[1][2], f[0][3] + f[1][3]), ktag);
        TL(st * 8 + 7);
      }
      if (q == 0 && st >= 0) exchange(st, 0, ln);
      if (st < 3) {
        const int row = par * 64 + q * 16 + (ln & 15);
        const uint32_t ra = sb + SM_A + row * 128 + ((((ln >> 4) * 4) ^ c) << 4);
        uint32_t shift = 0, ck = 0;
        float s1 = 0.f, s2 = 0.f;
        if (st == 0) {
#pragma unroll 1
          for (int u = q ? q + 2 : 11; u < 11; u += 3) {
            uint4 v[8];
            cs_load(v, M, u, ln);
            cs_total(v, M, u, ln, par, sb, BAR(B_CSG));
            TLW(13, u);
          }
        }
#pragma unroll 1
        for (int j = 0; j < 7; ++j) {
          const int kb = j ? j - 1 : 6;
          uint32_t v[4][4];
          mbar_wait(BAR(B_AFULL + 2 * j + par), (st & 1) ^ 1);
#pragma unroll
          for (int e = 0; e < 4; ++e) lds16((ra ^ (e * 16)) + kb * 16384, v[e]);
          if (j == 6) TL(st * 8 + 10);
          if (j == 4) TL(st * 8 + 9);
          if (j == 0) {
            uint32_t m[4];
#pragma unroll
            for (int e = 0; e < 4; ++e) m[e] = hadd2(hadd2(v[e][0], v[e][1]), hadd2(v[e][2], v[e][3]));
            const uint32_t ms = hadd2(hadd2(m[0], m[1]), hadd2(m[2], m[3]));
            float mf = (bf_lo(ms) + bf_hi(ms)) * (1.f / 64);
            mf += __shfl_xor_sync(~0u, mf, 16);
            shift = pack2(mf, mf);
          }
          uint32_t t[4], u[4];
#pragma unroll
          for (int e = 0; e < 4; ++e) {
            const uint32_t d0 = hsub2(v[e][0], shift), d1 = hsub2(v[e][1], shift), d2 = hsub2(v[e][2], shift), d3 = hsub2(v[e][3], shift);
            if (!safe) ck += (v[e][0] + v[e][1]) + (v[e][2] + v[e][3]);
            t[e] = hadd2(hadd2(d0, d1), hadd2(d2, d3));
            u[e] = hfma2(d3, d3, hfma2(d2, d2, hfma2(d1, d1, hmul2(d0, d0))));
          }
          const uint32_t ts = hadd2(hadd2(t[0], t[1]), hadd2(t[2], t[3])), us = hadd2(hadd2(u[0], u[1]), hadd2(u[2], u[3]));
          s1 += bf_lo(ts) + bf_hi(ts);
          s2 += bf_lo(us) + bf_hi(us);
        }
        const float dm = (s1 + __shfl_xor_sync(~0u, s1, 16)) * (1.f / DM);
        const float var = fmaxf(fmaf(-dm, dm, (s2 + __shfl_xor_sync(~0u, s2, 16)) * (1.f / DM)), 0.f);
        if (st < 0) cluster_wait();
        const uint32_t to = mapa(sb, ln >> 4);
        asm volatile("st.async.weak.shared::cluster.mbarrier::complete_tx::bytes.v2.f32 [%0], {%1,%2}, [%3];"
                     ::"r"(to + SM_STATS + row * 8), "f"(bf_lo(shift) + dm), "f"(rsqrt_fast(var + 1e-5f)), "r"(to + SM_BAR + 8 * (B_STATF + par)) : "memory");
        TL(st * 8 + 8);
        if (!safe && st >= 0) {
          uint32_t ep;
          asm volatile("ld.shared.u32 %0, [%1];" : "=r"(ep) : "r"(sb + SM_REDO + 4) : "memory");
          ep += st;
          ck += __shfl_xor_sync(~0u, ck, 1);
          ck += __shfl_xor_sync(~0u, ck, 2);
          ck += __shfl_xor_sync(~0u, ck, 16);
          if (!(ln & 19))
            asm volatile("{.reg .b64 u; mov.b64 u, {%1,%2}; st.relaxed.gpu.global.b64 [%0], u;}" ::"l"(&G.chk[row >> 2][p >> 1]), "r"(ck), "r"(ep) : "memory");
          int n = 0;
          while (__any_sync(~0u, ld_acquire(G.fin + c) != ep)) SPIN_GUARD(n);
          asm volatile("fence.proxy.async.global;" ::: "memory");
          const __nv_bfloat16* src = Q.out + (grp * 128 + 16 * p + 4 * q) * DM + 8 * ln;
          uint4 f[7];
          static_for<0, 7>([&](auto I) { f[I.value] = ld_ll_o<I.value * 512>(src); });
          uint2 cc;
          do {
            cc = ld_ll8_o<0>(&G.chk[4 * p + q][ln & 3]);
            SPIN_GUARD(n);
          } while (__any_sync(~0u, cc.y != ep));
          ck = 0;
#pragma unroll
          for (int e = 0; e < 7; ++e) ck += (f[e].x + f[e].y) + (f[e].z + f[e].w);
          ck = __reduce_add_sync(~0u, ck);
          if (cc.x != ck) asm volatile("st.shared.u32 [%0], %1;" ::"r"(sb + SM_REDO), "r"(1u) : "memory");
          __syncwarp();
          if (lane == 0) mbar_arrive(BAR(B_ADDED));
        }
      }
#pragma unroll
      for (int i = 0; i < 7; ++i) wv[i] = make_uint4(0u, 0u, 0u, 0u);
    }
  } else {
    asm volatile("setmaxnreg.dec.sync.aligned.u32 40;");
    const int qcol = 56 * p - 8 * par;
    if (elect_one()) {
      const int w = warp & 1, isx = warp & 2;
      const uint32_t bw = BAR(warp & 3), b0 = bw + 64 * isx;
      mbar_init(b0, 1);
      mbar_expect(b0, isx ? 8192 : QKV_BYTES);
      tma4d(isx ? sb + SM_A + 6 * 16384 + w * 8192 : sb + SM_RING + w * STG, isx ? &P.m_x : &P.m_qkv, isx ? 384 : qcol,
            isx ? grp * 128 + w * 64 : 384 + 32 * w, 0, 0, b0);
      TLW(14, 20 + warp);
      mbar_init(bw + 128 - 64 * isx, 1);
#pragma unroll
      for (int i = 1; i < 12; ++i)
        if (i != 4) mbar_init(bw + 32 * i, i > 9 ? 4 : i == 9 ? 5 : (i & 14) == 2 ? 8 : 1);
      mbar_init(bw + 384, isx ? 1 : 4 + w);
      fence_async();
      asm volatile("fence.mbarrier_init.release.cluster;" ::: "memory");
    }
    __syncwarp();
    cluster_arrive();
    asm volatile("bar.arrive 4, 256;" ::: "memory");
    asm volatile("bar.arrive 5, 384;" ::: "memory");
    bar_sync(3, 128);
    TLW(14, 24 + warp);
    if (warp == 12) {
      {
        uint32_t bar = BAR(B_FULL), d = sb + SM_RING, ph = 0;
        const uint32_t bar_end = BAR(B_FULL + NRING);
        auto acquire = [&](uint32_t bytes) {
          mbar_wait(bar + 8 * B_EMPTY, ph);
          expect1(bar, bytes);
        };
        auto adv = [&] {
          bar += 8;
          d += STG;
          if (bar == bar_end) { bar -= 8 * NRING; d -= NRING * STG; ph ^= 1; }
        };
        const int atom0 = 7 * (p >> 1) + 4 * par;
#pragma unroll 1
        for (int l = 0; l < 2; ++l) {
#pragma unroll 1
          for (int k0 = l ? 0 : 32 * NRING; k0 < 448; k0 += 32) {
            acquire(QKV_BYTES);
            tma4d1(d, &P.m_qkv + l, l ? 0 : qcol, (k0 < 64 ? k0 + 384 : k0 - 64) + 448 * p * l, 0, 0, bar);
            if (l == 0) TLW(12, 48 + (k0 >> 5));
            adv();
          }
          const uint32_t lastb = bar + 8 * B_EMPTY - 8, lastp = ph ^ 1;
#pragma unroll 1
          for (int k1 = 352; k1 < 832; k1 += 32) {
            const int k0 = k1 < 448 ? k1 : k1 - 448;
            if (k1 == 352 + 32 * EARLY * l) {
          mbar_wait(lastb, lastp);
          expect1(BAR(B_WO), 57344);
#pragma unroll 1
          for (int i = 0; i < 5; ++i)
            tma4d1(i < 3 ? sb + SM_A + i * 32768 + (par ^ 1) * 16384 : sb + SM_RING + 12288 + (i - 3) * STG, i < 3 ? &P.m_wo : &P.m_woh,
                   i < 3 ? 128 * i + 64 * par : 384, 0, i == 4, i < 3 ? p & 6 : p, BAR(B_WO));
          mbar_wait(BAR(B_WO), l);
          if (l == 0) {
            int n = 0;
            while (__any_sync(~0u, ld_acquire(M.pk + (lane & 15)) != 1u)) SPIN_GUARD(n);
            asm volatile("fence.proxy.async.global;" ::: "memory");
            TLW(12, 62);
          }
            }
            if (k1 == 352) {
              acquire(16384);
              tma4d1(d, &P.m_gu2[0], 0, 384, atom0, 0, bar);
              if (two) tma4d1(d + 8192, &P.m_gu2[1], 0, 384, atom0, 0, bar);
              adv();
              continue;
            }
            acquire(12288);
            tma4d1(d, &P.m_gu1[0], 0, k0, atom0 + 2, 0, bar);
            if (two) tma4d1(d + 4096, &P.m_gu1[1], 0, k0, atom0 + 2, 0, bar);
            tma4d1(d + 8192, &P.m_guh, 0, k0 + 448 * p, 3, 0, bar);
            adv();
          }
#pragma unroll 1
          for (int ps = 0; ps < 2; ++ps) {
            int k0 = 128 * ps;
#pragma unroll 1
            do {
              acquire(16384);
              tma4d1(d, &P.m_gu2[0], 0, k0, atom0 + ps, 0, bar);
              if (two) tma4d1(d + 8192, &P.m_gu2[1], 0, k0, atom0 + ps, 0, bar);
              adv();
              k0 = k0 == 384 ? 0 : k0 + 64;
            } while (k0 != 384 - 256 * ps);
          }
#pragma unroll 1
          for (int it = -2; it < 12; ++it) {
            const int n0 = it < 0 ? 384 : 64 * par + 32 * (it & 12), m = p ^ (it > 0 && (it & 2)), k0 = 224 * m + 32 * (m & 1);
            if (it & 1) {
              acquire(16384);
              tma4d1(d, &P.m_wd128, n0, k0, 0, 0, bar);
            } else {
              acquire(12288);
              tma4d1(d, &P.m_wd64, n0, k0 + 128, 0, 0, bar);
              tma4d1(d + 8192, &P.m_wd32, n0, (m & 1) ? 224 * m : 224 * m + 192, 0, 0, bar);
            }
            adv();
          }
          mbar_wait(BAR(B_COPIED), 0);
        }
      }
    } else {
      const int g = warp - 13;
      if (g == 2) cluster_wait();
      if (g == 2 && elect_one()) {
        const uint32_t tx0 = clock();
#pragma unroll 1
        for (int i = 2; i < 14; ++i) {
          const int kb = (i >> 1) - 1, b = i - 2;
          if (!(i & 1)) while ((int)(clock() - tx0) < (i >> 1) * XB - XB0) {}
          mbar_expect(BAR(B_AFULL + i), 8192);
          if ((i & 1) == par) tma4d_mc(sb + SM_A + b * 8192, &P.m_x, 64 * kb, grp * 128 + par * 64, BAR(B_AFULL + i));
          TLW(14, 48 + i);
          if (i < NRING) {
            mbar_expect(BAR(B_FULL + i), QKV_BYTES);
            tma4d(sb + SM_RING + i * STG, &P.m_qkv, qcol, 32 * i - 64, 0, 0, BAR(B_FULL + i));
            TLW(12, 48 + i);
          }
        }
      }
      __syncwarp();
      const int step = g == 2 ? 3 : 2 - g;
      const uint32_t rseq = ld_flag(G.rdy + p) + 1;
      const uint32_t vbase = ld_flag(Q.S->sync);
      float ms0 = 0.f;
      bool redo = false;
      const int mcol = 448 * (p >> 1) + 192 + 32 * par;
      if (g < 2) {
        const int ds = lane - 4 * g;
        uint2 wv[8];
#pragma unroll
        for (int e = 0; e < 8; ++e) wv[e] = make_uint2(0u, 0u);
        if (ds >= 0 && ds < 28) {
          const uint2* src = (const uint2*)((const char*)Q.wphi + ((2 * p + g) * 784 + ds * 28) * 2);
#pragma unroll
          for (int e = 0; e < 8; ++e) wv[e] = __ldg(src + (e == 0 ? 0 : e == 7 ? 6 : e - g));
        }
#pragma unroll
        for (int ch = 0; ch < 4; ++ch)
          sts16(sb + SM_WPHI + g * 2048 + lane * 64 + ((ch ^ ((lane >> 1) & 3)) << 4),
                make_uint4(wv[2 * ch].x, wv[2 * ch].y, wv[2 * ch + 1].x, wv[2 * ch + 1].y));
        if (!safe) sts16(sb + SM_BAR0 + 448, make_uint4(1u, 0u, 0u, 0u));
        fence_async();
        __syncwarp();
        if (lane == 0) mbar_arrive(BAR(B_CSF));
      }
      if (g == 0) {
        mbar_wait(BAR(PK_T), 0);
        const __nv_bfloat16* src = (lane & 4 ? Q.wu : Q.wg) + (28 * grp + (lane >> 3)) * FF + mcol + 8 * (lane & 3);
        uint4* dst = Q.S->wq + (p * 448 + 28 * grp + (lane >> 3)) * 32 + 24 + (lane & 7);
        uint4 v[7];
#pragma unroll
        for (int e = 0; e < 7; ++e) v[e] = ld_nc16(src + e * 4 * FF);
#pragma unroll
        for (int e = 0; e < 7; ++e) dst[e * 128] = v[e];
        TLW(12, 42);
        asm volatile("fence.proxy.async.global;" ::: "memory");
        __syncwarp();
        TLW(12, 46);
        if (elect_one()) st_release(M.pk + grp, 1u);
        __syncwarp();
        TLW(12, 47);
      }
      if (g == 2) {
        mbar_wait(BAR(PF_T), 0);
#pragma unroll 1
        for (int i = lane; i < 3 * 98; i += 32) {
          const char* w = (const char*)(i < 98 ? Q.wg : i < 196 ? Q.wu : P.wd);
          asm volatile("prefetch.global.L2 [%0];" ::"l"(w + bid * 12544 + (i % 98) * 128));
        }
      }
      static_assert(NRING == 6 && B_FULL == 0, "barrier layout");
#pragma unroll 1
      for (int st = 0; st < 4; ++st) {
        const int lane = opaque(tid & 31);
        if (g == 1) {
          int n = 0;
          if (st == 0) {
            const uint32_t bar = BAR(B_AFULL + (p < 6 ? 2 * p + 2 : 0));
            mbar_wait(bar, 0);
            mbar_wait(bar + 8, 0);
            mbar_wait(BAR(XC_T), 0);
            if (elect_one()) {
              if (p < 7) {
                tma_store(&P.m_o64, 64 * p, grp * 128, sb + SM_A + p * 16384);
                tma_store(&P.m_o64, 64 * p, grp * 128 + 64, sb + SM_A + p * 16384 + 8192);
              }
              asm volatile("st.shared.v2.u32 [%0], {%1,%2};" ::"r"(sb + SM_REDO), "r"(0u), "r"(rseq + 1) : "memory");
              bulk_read();
              mbar_arrive(BAR(B_CSF));
              bulk_done();
            }
          } else if constexpr (safe) {
#pragma unroll 1
            for (int j = 0; j < 7; ++j) mbar_wait(BAR(B_AFULL + 2 * j + par), st & 1);
          } else {
            mbar_wait(BAR(B_ADDED), 0);
            mbar_wait(BAR(B_AFULL + 10), st & 1);
            if (elect_one()) st_release(G.fin + p, rseq + st);
            mbar_wait(BAR(B_ADDED), 1);
          }
          __syncwarp();
          if (elect_one()) {
            if (st == 0) __threadfence();
            st_flag(G.rdy + p, rseq + st);
          }
          if constexpr (!safe) {
            mbar_wait(BAR(B_STATF), st & 1);
            mbar_wait(BAR(B_STATF + 1), st & 1);
            float ms = 0.f;
#pragma unroll
            for (int e = 0; e < 4; ++e) {
              const float2 v = lds8(sb + SM_STATS + e * 256 + lane * 8);
              ms += fmaf(v.x, v.x, rcp_fast(v.y * v.y));
            }
#pragma unroll
            for (int m = 1; m < 32; m <<= 1) ms += __shfl_xor_sync(~0u, ms, m);
            if (st == 0) ms0 = 4.f * ms;
            else redo |= !(ms >= ms0);
            if (st == 3 && lane == 0) {
              uint32_t bad;
              asm volatile("ld.shared.u32 %0, [%1];" : "=r"(bad) : "r"(sb + SM_REDO) : "memory");
              atomicAdd(Q.S->sync, redo || bad ? 0x10001u : 1u);
            }
          }
          mbar_wait(BAR(B_AFREE), st & 1);
          while (__any_sync(~0u, ld_acquire(G.rdy + (lane & 7)) != rseq + st)) SPIN_GUARD(n);
          if (lane < 4) mbar_arrive(BAR(B_STAGED + lane));
          TLW(15, st);
          if (!safe && st == 3) {
            uint32_t d;
            while (__any_sync(~0u, ((d = ld_flag(Q.S->sync) - vbase) & 0xffffu) != 128u)) SPIN_GUARD(n);
            if (lane == 0) {
              asm volatile("st.shared.u32 [%0], %1;" ::"r"(sb + SM_REDO), "r"(d >> 16) : "memory");
              mbar_arrive(BAR(B_VERDICT));
            }
          }
        }
        exchange(st, step, lane);
        if (g == 0 && st == 0) {
          const int c = lane & 7;
          const __nv_bfloat16* src = Q.wqkv + (28 * grp + (lane >> 3)) * 1344 + qcol + 8 * c;
          uint4* dst = Q.S->wq + (p * 448 + 28 * grp + (lane >> 3)) * 32 + c;
#pragma unroll 1
          for (int i = 0; i < 7; ++i) {
            uint4 v[3];
#pragma unroll
            for (int e = 0; e < 3; ++e) v[e] = ld_nc16(src + e * 448);
#pragma unroll
            for (int e = 0; e < 3; ++e) dst[e * 8] = v[e];
            src += 4 * 1344;
            dst += 128;
          }
          TLW(12, 43);
          asm volatile("fence.proxy.async.global;" ::: "memory");
          __syncwarp();
          if (elect_one()) st_release(M.pk + 16 + grp, 1u);
          __syncwarp();
          TLW(12, 45);
          mbar_wait(BAR(B_AFREE2), 0);
          int n = 0;
          while (__any_sync(~0u, ld_acquire(M.pk + 16 + (lane & 15)) != 1u)) SPIN_GUARD(n);
          asm volatile("fence.proxy.async.global;" ::: "memory");
          __syncwarp();
          if (lane == 0) mbar_arrive(BAR(B_COPIED));
          TLW(12, 44);
        }
      }
    }
  }
}

template <bool two>
__global__ void __cluster_dims__(2, 1, 1) __launch_bounds__(NTHREADS, 1) fused_kernel(const __grid_constant__ Ptrs Q, const __grid_constant__ Params P) {
  const uint32_t sb = s2u(smem_raw);
  if (sb & 1023u) __trap();
  run<two, false>(Q, P, sb, threadIdx.x, blockIdx.x);
  __syncwarp();
  uint32_t s2, tid, bid;
  asm volatile("mov.u32 %0, smem_raw; mov.u32 %1, %%tid.x; mov.u32 %2, %%ctaid.x;" : "=r"(s2), "=r"(tid), "=r"(bid));
  mbar_wait(s2 + SM_BAR0 + 8 * B_VERDICT, 0);
  uint32_t redo;
  asm volatile("ld.shared.u32 %0, [%1];" : "=r"(redo) : "r"(s2 + SM_REDO) : "memory");
  if (__any_sync(~0u, redo)) {
    if (tid < 256) {
      asm volatile("setmaxnreg.dec.sync.aligned.u32 128;");
    } else {
      asm volatile("setmaxnreg.inc.sync.aligned.u32 128;");
      if (tid >= 384 && tid < 480) cluster_wait();
    }
    __threadfence();
    __syncthreads();
    if (tid < 32) {
      uint32_t t = 0;
      if (tid == 0) { __threadfence(); t = (atomicAdd(Q.S->sync + 32, 1u) | 127u) + 1u; }
      t = __shfl_sync(~0u, t, 0);
      int n = 0;
      while (__any_sync(~0u, ld_acquire(Q.S->sync + 32) != t)) SPIN_GUARD(n);
    }
    asm volatile("fence.proxy.async;" ::: "memory");
    __syncthreads();
    const int role = __shfl_sync(~0u, tid >> 7, 0);
    static_for<0, 3>([&](auto R) {
      if (R.value ? role == R.value + 1 : role < 2) {
        asm volatile("mov.u32 %0, smem_raw; mov.u32 %1, %%tid.x; mov.u32 %2, %%ctaid.x;" : "=r"(s2), "=r"(tid), "=r"(bid));
        run<two, true, R.value>(Q, P, R.value ? s2 : sb, tid, bid);
        asm volatile("exit;");
      }
    });
  }
}

typedef CUresult (*EncodeFn)(CUtensorMap*, CUtensorMapDataType, cuuint32_t, void*, const cuuint64_t*, const cuuint64_t*,
                             const cuuint32_t*, const cuuint32_t*, CUtensorMapInterleave, CUtensorMapSwizzle,
                             CUtensorMapL2promotion, CUtensorMapFloatOOBfill);

static bool make_map(EncodeFn fn, CUtensorMap* m, const void* ptr, int rank, const cuuint64_t* dims, const cuuint64_t* strides,
                     const cuuint32_t* box, CUtensorMapSwizzle sw) {
  const cuuint32_t es[4] = {1, 1, 1, 1};
  cuuint64_t d4[4], s4[3];
  cuuint32_t b4[4];
  for (int i = 0; i < 4; ++i) { d4[i] = i < rank ? dims[i] : 1; b4[i] = i < rank ? box[i] : 1; }
  for (int i = 0; i < 3; ++i) s4[i] = i + 1 < rank ? strides[i] : strides[0] * dims[1];
  return fn(m, CU_TENSOR_MAP_DATA_TYPE_BFLOAT16, 4, (void*)ptr, d4, s4, b4, es, CU_TENSOR_MAP_INTERLEAVE_NONE, sw,
            CU_TENSOR_MAP_L2_PROMOTION_L2_128B, CU_TENSOR_MAP_FLOAT_OOB_FILL_NONE) == CUDA_SUCCESS;
}

}

extern "C" void kernel_launch(void* const* d_in, const int* in_sizes, int n_in, void* d_out, int out_size) {
  using namespace hk;
  (void)in_sizes; (void)n_in; (void)out_size;
  static EncodeFn fn = nullptr;
  static Scratch* scr = nullptr;
  if (!fn) {
    cudaGetSymbolAddress((void**)&scr, g_scr);
    void* f = nullptr;
    cudaDriverEntryPointQueryResult qr;
    cudaGetDriverEntryPoint("cuTensorMapEncodeTiled", &f, cudaEnableDefault, &qr);
    fn = (EncodeFn)f;
    cudaFuncSetAttribute(fused_kernel<false>, cudaFuncAttributeMaxDynamicSharedMemorySize, SM_TOTAL + TL_EXTRA);
    cudaFuncSetAttribute(fused_kernel<true>, cudaFuncAttributeMaxDynamicSharedMemorySize, SM_TOTAL + TL_EXTRA);
  }
  Params P;
  Ptrs Q;
  Q.S = scr;
  void *const upd = scr->upd, *const wq = scr->wq;
  Q.wqkv = (const __nv_bfloat16*)d_in[1];
  Q.wphi = (const __nv_bfloat16*)d_in[2];
  Q.wg = (const __nv_bfloat16*)d_in[5];
  Q.wu = (const __nv_bfloat16*)d_in[6];
  P.wd = (const __nv_bfloat16*)d_in[7];
  Q.out = (__nv_bfloat16*)d_out;
  bool ok = true, two = false;
  {
    const cuuint64_t d[2] = {448, 2048}, s[1] = {896};
    const cuuint32_t b[2] = {64, 64};
    ok &= make_map(fn, &P.m_x, d_in[0], 2, d, s, b, CU_TENSOR_MAP_SWIZZLE_128B);
    ok &= make_map(fn, &P.m_o64, Q.out, 2, d, s, b, CU_TENSOR_MAP_SWIZZLE_128B);
    ok &= make_map(fn, &P.m_upd, upd, 2, d, s, b, CU_TENSOR_MAP_SWIZZLE_128B);
  }
  {
    const cuuint64_t d[3] = {448, 448, 3}, s[2] = {2688, 896};
    const cuuint32_t b[3] = {64, 32, 3};
    ok &= make_map(fn, &P.m_qkv, Q.wqkv, 3, d, s, b, CU_TENSOR_MAP_SWIZZLE_128B);
    const cuuint64_t d2[3] = {64, 8 * 448, 4}, s2[2] = {512, 128};
    const cuuint32_t bh[3] = {64, 32, 1};
    ok &= make_map(fn, &P.m_qkv2, wq, 3, d2, s2, b, CU_TENSOR_MAP_SWIZZLE_128B);
    ok &= make_map(fn, &P.m_guh, wq, 3, d2, s2, bh, CU_TENSOR_MAP_SWIZZLE_128B);
  }
  {
    const cuuint64_t d[4] = {448, 32, 2, 8}, s[3] = {896, 24 * 896, 56 * 896};
    const cuuint32_t b[4] = {64, 32, 2, 2}, bh[4] = {64, 32, 1, 1};
    ok &= make_map(fn, &P.m_wo, d_in[3], 4, d, s, b, CU_TENSOR_MAP_SWIZZLE_128B);
    ok &= make_map(fn, &P.m_woh, d_in[3], 4, d, s, bh, CU_TENSOR_MAP_SWIZZLE_128B);
  }
  {
    const cuuint64_t delta = (cuuint64_t)((const char*)Q.wu - (const char*)Q.wg);
    bool merged = (const char*)Q.wg < (const char*)Q.wu && delta % 16 == 0 && delta < (1ull << 40);
    for (int pass = merged ? 0 : 1; pass < 2; ++pass) {
      const cuuint32_t np = pass == 0 ? 2 : 1;
      const cuuint64_t d[4] = {64, 448, 28, np}, s[3] = {3584, 128, pass == 0 ? delta : 3584 * 448};
      const cuuint32_t b2[4] = {64, 64, 1, np}, b1[4] = {64, 32, 1, np};
      bool good = true;
      for (int u = 0; u < 2; ++u) {
        const void* w = u && pass ? Q.wu : Q.wg;
        good &= make_map(fn, &P.m_gu2[u], w, 4, d, s, b2, CU_TENSOR_MAP_SWIZZLE_128B);
        good &= make_map(fn, &P.m_gu1[u], w, 4, d, s, b1, CU_TENSOR_MAP_SWIZZLE_128B);
      }
      two = pass;
      if (good) break;
      if (pass) ok = false;
    }
  }
  {
    const cuuint64_t d[2] = {448, 1792}, s[1] = {896};
    const cuuint32_t b128[2] = {64, 128}, b64[2] = {64, 64}, b32[2] = {64, 32};
    ok &= make_map(fn, &P.m_wd128, P.wd, 2, d, s, b128, CU_TENSOR_MAP_SWIZZLE_128B);
    ok &= make_map(fn, &P.m_wd64, P.wd, 2, d, s, b64, CU_TENSOR_MAP_SWIZZLE_128B);
    ok &= make_map(fn, &P.m_wd32, P.wd, 2, d, s, b32, CU_TENSOR_MAP_SWIZZLE_128B);
  }
  if (!ok) return;
  if (!two) fused_kernel<false><<<128, NTHREADS, SM_TOTAL + TL_EXTRA>>>(Q, P);
  else fused_kernel<true><<<128, NTHREADS, SM_TOTAL + TL_EXTRA>>>(Q, P);
}
```
